```python
import torch

def _softmax(x, axis=-1):
    return torch.softmax(x, dim=axis)
def _gelu(x):
    return torch.nn.functional.gelu(x, approximate="tanh")
def _silu(x):
    return torch.nn.functional.silu(x)
def _sigmoid(x):
    return torch.sigmoid(x)
def _layernorm(x, axis=-1, eps=1e-5):
    m = x.mean(dim=axis, keepdim=True)
    v = x.var(dim=axis, keepdim=True, unbiased=False)
    return (x - m) / torch.sqrt(v + eps)
def _scatter_add(tgt, idx, src, axis=0):
    return tgt.clone().index_add_(axis, idx, src)
def _segment_sum(src, seg, n):
    out = torch.zeros((n,) + src.shape[1:], dtype=src.dtype)
    return out.index_add_(0, seg, src)
def _pad(x, pw):
    flat = tuple(v for pair in reversed(pw) for v in pair)
    return torch.nn.functional.pad(x, flat)

kernel_name = 'standalone__kv_cache_quant_int4_int2_kv_with_per_channel_or_per_token_scales__prompt'

def setup_inputs():

    _w = (lambda a: (lambda t: t.to(torch.bfloat16) if t.is_floating_point() else t)(torch.as_tensor(a)))
    B = 1
    Sq = 2048
    Skv = 2048
    Hq = 32
    Hkv = 8
    Dh = 128
    bits = 8
    G = -1
    if G <= 0 or G >= Skv:
        G = max(1, Skv // 2)
    Skv = (Skv // G) * G
    ngk = Skv // G
    qmax = (1 << bits) - 1
    return {
        "q": _w((lambda *s: torch.randn(*s, dtype=torch.bfloat16) * 0.2)(B, Hq, Sq, Dh)),
        "qk": _w(torch.randint(0, qmax + 1, (B, Hkv, Skv, Dh)).to(torch.int32)),
        "qv": _w(torch.randint(0, qmax + 1, (B, Hkv, Skv, Dh)).to(torch.int32)),
        "k_scales": _w(torch.abs((lambda *s: torch.randn(*s, dtype=torch.bfloat16) * 0.2)(B, Hkv, ngk, Dh)) * 0.05 + 0.02),
        "k_zeros": _w((lambda *s: torch.randn(*s, dtype=torch.bfloat16) * 0.2)(B, Hkv, ngk, Dh) + float(qmax) / 2.0),
        "v_scales": _w(torch.abs((lambda *s: torch.randn(*s, dtype=torch.bfloat16) * 0.05)(B, Hkv, Skv, 1)) * 0.05 + 0.02),
        "v_zeros": _w((lambda *s: torch.randn(*s, dtype=torch.bfloat16) * 0.05)(B, Hkv, Skv, 1) + float(qmax) / 2.0),
    }

def reference(q, qk, qv, k_scales, k_zeros, v_scales, v_zeros):
    B, Hq, Sq, Dh = q.shape
    Hkv, Skv = qk.shape[1], qk.shape[2]
    ngk = k_scales.shape[2]
    G = Skv // ngk
    ks = (lambda x, n, axis: torch.repeat_interleave(x, n, dim=axis))(k_scales, G, axis=2)
    kz = (lambda x, n, axis: torch.repeat_interleave(x, n, dim=axis))(k_zeros, G, axis=2)
    k = ((lambda x, dt: x.to(dt))(qk, q.dtype) - kz) * ks
    v = ((lambda x, dt: x.to(dt))(qv, q.dtype) - v_zeros) * v_scales
    rep = Hq // Hkv
    if rep > 1:
        k = (lambda x, n, axis: torch.repeat_interleave(x, n, dim=axis))(k, rep, axis=1)
        v = (lambda x, n, axis: torch.repeat_interleave(x, n, dim=axis))(v, rep, axis=1)
    scale = float(Dh) ** -0.5
    logits = torch.einsum("bhqd,bhkd->bhqk", q, k) * scale
    p = _softmax(logits, axis=-1)
    o = torch.einsum("bhqk,bhkd->bhqd", p, v)
    return o
```

```cpp
#include <cuda_runtime.h>
#include <cuda_bf16.h>
#include <cuda.h>
#include <stdint.h>

#define PIN_J 7
#define FLUSH_N 2
#define FORCE_CLUSTERS 0

namespace {

constexpr int HQ = 32, HKV = 8, SEQ = 2048, DH = 128, NGK = 2, GRP = SEQ / NGK;
constexpr int BN = 128, NBLK = SEQ / BN;
constexpr int TILE_BYTES = BN * DH * 2;
constexpr int NS = 6;
constexpr int NTILES = HQ * SEQ / 256;
constexpr int TILES_PER_HEAD = NTILES / HKV;
constexpr int QBUF_BYTES = 128 * DH * 2;
constexpr int SMEM_BYTES = NS * TILE_BYTES + QBUF_BYTES + 1024;
constexpr int UNITS_PER_HEAD = 2 * NBLK;
constexpr int ITEMS_PER_UNIT = 32;
constexpr int NITEMS = HKV * UNITS_PER_HEAD * ITEMS_PER_UNIT;
constexpr int ITEMS_PER_CHUNK = 16;
constexpr int NCHUNKS = NITEMS / ITEMS_PER_CHUNK;
constexpr int NIN = 4;
constexpr float SCALE_LOG2 = 0.08838834764831845f * 1.4426950408889634f;
constexpr float L_MIN = 9.094947017729282e-13f, L_MAX = 1099511627776.0f;

__device__ __align__(1024) uint4 g_kv[2 * HKV * NBLK * (TILE_BYTES / 16)];
__device__ __align__(128) unsigned int g_cnt[HKV * UNITS_PER_HEAD];
__device__ unsigned int g_done;

#define DBG_IT(i)
#define DBG_STAMP(i)
#define DBG_T(k)

__device__ __forceinline__ uint32_t smem_u32(const void* p) { return (uint32_t)__cvta_generic_to_shared(p); }

__device__ __forceinline__ void mbar_init(uint32_t a, uint32_t cnt) {
    asm volatile("mbarrier.init.shared::cta.b64 [%0], %1;" ::"r"(a), "r"(cnt) : "memory");
}
__device__ __forceinline__ void mbar_expect_tx(uint32_t a, uint32_t bytes) {
    asm volatile("mbarrier.arrive.expect_tx.shared::cta.b64 _, [%0], %1;" ::"r"(a), "r"(bytes) : "memory");
}
__device__ __forceinline__ void mbar_wait(uint32_t a, uint32_t parity) {
    asm volatile(
        "{\n"
        ".reg .pred p;\n"
        ".reg .u32 n;\n"
        "mbarrier.try_wait.parity.shared::cta.b64 p, [%0], %1;\n"
        "@p bra WAIT_DONE;\n"
        "mov.u32 n, 0;\n"
        "WAIT_LOOP:\n"
        "mbarrier.try_wait.parity.shared::cta.b64 p, [%0], %1;\n"
        "@p bra WAIT_DONE;\n"
        "add.u32 n, n, 1;\n"
        "setp.lt.u32 p, n, 0x1000000;\n"
        "@p bra WAIT_LOOP;\n"
        "trap;\n"
        "WAIT_DONE:\n"
        "}\n" ::"r"(a), "r"(parity) : "memory");
}
__device__ __forceinline__ uint32_t mbar_test(uint32_t a, uint32_t parity) {
    uint32_t ok;
    asm volatile("{\n.reg .pred p;\nmbarrier.test_wait.parity.shared::cta.b64 p, [%1], %2;\nselp.u32 %0, 1, 0, p;\n}\n"
                 : "=r"(ok) : "r"(a), "r"(parity) : "memory");
    return ok;
}
__device__ __forceinline__ void mbar_arrive(uint32_t a) {
    asm volatile("mbarrier.arrive.shared::cta.b64 _, [%0];" ::"r"(a) : "memory");
}
__device__ __forceinline__ uint32_t mapa(uint32_t a, uint32_t cta) {
    uint32_t r; asm("mapa.shared::cluster.u32 %0, %1, %2;" : "=r"(r) : "r"(a), "r"(cta)); return r;
}
__device__ __forceinline__ void mbar_arrive_remote(uint32_t ra) {
    asm volatile("mbarrier.arrive.shared::cluster.b64 _, [%0];" ::"r"(ra) : "memory");
}
__device__ __forceinline__ void bulk_load(uint32_t dst, const void* src, uint32_t bytes, uint32_t bar) {
    asm volatile("cp.async.bulk.shared::cluster.global.mbarrier::complete_tx::bytes [%0], [%1], %2, [%3];"
        ::"r"(dst), "l"(src), "r"(bytes), "r"(bar) : "memory");
}
__device__ __forceinline__ void bulk_load_hint(uint32_t dst, const void* src, uint32_t bytes, uint32_t bar, uint64_t pol) {
    asm volatile("cp.async.bulk.shared::cluster.global.mbarrier::complete_tx::bytes.L2::cache_hint [%0], [%1], %2, [%3], %4;"
        ::"r"(dst), "l"(src), "r"(bytes), "r"(bar), "l"(pol) : "memory");
}
__device__ __forceinline__ void bulk_load_mc(uint32_t dst, const void* src, uint32_t bytes, uint32_t bar, uint16_t mask) {
    asm volatile("cp.async.bulk.shared::cluster.global.mbarrier::complete_tx::bytes.multicast::cluster [%0], [%1], %2, [%3], %4;"
        ::"r"(dst), "l"(src), "r"(bytes), "r"(bar), "h"(mask) : "memory");
}
__device__ __forceinline__ void bulk_store(void* dst, uint32_t src, uint32_t bytes) {
    asm volatile("cp.async.bulk.global.shared::cta.bulk_group [%0], [%1], %2;" ::"l"(dst), "r"(src), "r"(bytes) : "memory");
}
__device__ __forceinline__ void tma_load_2d(uint32_t dst, const CUtensorMap* map, int c0, int c1, uint32_t bar) {
    asm volatile("cp.async.bulk.tensor.2d.shared::cluster.global.mbarrier::complete_tx::bytes [%0], [%1, {%3, %4}], [%2];"
        ::"r"(dst), "l"(map), "r"(bar), "r"(c0), "r"(c1) : "memory");
}
__device__ __forceinline__ void cluster_arrive() { asm volatile("barrier.cluster.arrive.relaxed.aligned;" ::: "memory"); }
__device__ __forceinline__ void cluster_arrive_release() { asm volatile("barrier.cluster.arrive.release.aligned;" ::: "memory"); }
__device__ __forceinline__ void cluster_wait() { asm volatile("barrier.cluster.wait.aligned;" ::: "memory"); }
__device__ __forceinline__ void wg_fence() { asm volatile("wgmma.fence.sync.aligned;" ::: "memory"); }
__device__ __forceinline__ void wg_commit() { asm volatile("wgmma.commit_group.sync.aligned;" ::: "memory"); }
template <int N> __device__ __forceinline__ void wg_wait() { asm volatile("wgmma.wait_group.sync.aligned %0;" ::"n"(N) : "memory"); }
__device__ __forceinline__ void bar_sync(int id, int n) { asm volatile("bar.sync %0, %1;" ::"r"(id), "r"(n) : "memory"); }
__device__ __forceinline__ void bar_arrive(int id, int n) { asm volatile("bar.arrive %0, %1;" ::"r"(id), "r"(n) : "memory"); }

__device__ __forceinline__ float ex2(float x) { float y; asm("ex2.approx.ftz.f32 %0, %1;" : "=f"(y) : "f"(x)); return y; }
__device__ __forceinline__ uint32_t pack_bf16(float lo, float hi) {
    uint32_t r; asm("cvt.rn.bf16x2.f32 %0, %1, %2;" : "=r"(r) : "f"(hi), "f"(lo)); return r;
}
__device__ __forceinline__ uint32_t bf2_sub(uint32_t a, uint32_t b) { uint32_t r; asm("sub.rn.bf16x2 %0, %1, %2;" : "=r"(r) : "r"(a), "r"(b)); return r; }
__device__ __forceinline__ uint32_t bf2_mul(uint32_t a, uint32_t b) { uint32_t r; asm("mul.rn.bf16x2 %0, %1, %2;" : "=r"(r) : "r"(a), "r"(b)); return r; }
__device__ __forceinline__ uint32_t bf2_fma(uint32_t a, uint32_t b, uint32_t c) { uint32_t r; asm("fma.rn.bf16x2 %0, %1, %2, %3;" : "=r"(r) : "r"(a), "r"(b), "r"(c)); return r; }

#define F8(a, i) "+f"(a[i]), "+f"(a[i + 1]), "+f"(a[i + 2]), "+f"(a[i + 3]), "+f"(a[i + 4]), "+f"(a[i + 5]), "+f"(a[i + 6]), "+f"(a[i + 7])
#define F64(a) F8(a, 0), F8(a, 8), F8(a, 16), F8(a, 24), F8(a, 32), F8(a, 40), F8(a, 48), F8(a, 56)

template <int TB>
__device__ __forceinline__ void wgmma_rs(float (&d)[64], uint32_t a0, uint32_t a1, uint32_t a2, uint32_t a3, uint64_t desc, int scale_d) {
    asm volatile(
        "{\n.reg .pred p;\nsetp.ne.b32 p, %69, 0;\n"
        "wgmma.mma_async.sync.aligned.m64n128k16.f32.bf16.bf16 "
        "{%0,%1,%2,%3,%4,%5,%6,%7,%8,%9,%10,%11,%12,%13,%14,%15,"
        "%16,%17,%18,%19,%20,%21,%22,%23,%24,%25,%26,%27,%28,%29,%30,%31,"
        "%32,%33,%34,%35,%36,%37,%38,%39,%40,%41,%42,%43,%44,%45,%46,%47,"
        "%48,%49,%50,%51,%52,%53,%54,%55,%56,%57,%58,%59,%60,%61,%62,%63},"
        "{%64,%65,%66,%67}, %68, p, 1, 1, %70;\n}\n"
        : F64(d)
        : "r"(a0), "r"(a1), "r"(a2), "r"(a3), "l"(desc), "r"(scale_d), "n"(TB));
}
__device__ __forceinline__ void fence_regs(float (&d)[64]) {
#pragma unroll
    for (int i = 0; i < 64; i++) asm volatile("" : "+f"(d[i])::"memory");
}
__device__ __forceinline__ void fence_regs(uint32_t (&d)[32]) {
#pragma unroll
    for (int i = 0; i < 32; i++) asm volatile("" : "+r"(d[i])::"memory");
}

struct DqItem { int kv, head, p, tok; };
__device__ __forceinline__ DqItem item_decode(int it, int h0, int h0inv) {
    DqItem d;
    const int su = it / ITEMS_PER_UNIT, part = it % ITEMS_PER_UNIT;
    if (su < UNITS_PER_HEAD * h0) { d.p = (su * h0inv) >> 16; d.head = su - d.p * h0; }
    else { const int x = su - UNITS_PER_HEAD * h0; d.head = h0 + x / UNITS_PER_HEAD; d.p = x % UNITS_PER_HEAD; }
    int blk;
    if (d.p == 0) { d.kv = 0; blk = 0; }
    else if (d.p == UNITS_PER_HEAD - 1) { d.kv = 1; blk = NBLK - 1; }
    else if (d.p & 1) { d.kv = 0; blk = (d.p + 1) >> 1; }
    else { d.kv = 1; blk = (d.p >> 1) - 1; }
    d.tok = blk * BN + part * 4;
    return d;
}
struct DqPtrs {
    const int* qk; const int* qv;
    const __nv_bfloat16 *ks, *kz, *vs, *vz;
};
__device__ __forceinline__ uint8_t* kv_tile(int kv, int head, int blk) {
    return reinterpret_cast<uint8_t*>(g_kv) + (size_t)((kv * HKV + head) * NBLK + blk) * TILE_BYTES;
}
__device__ __forceinline__ uint32_t codes_bf2(int a, int b) { return pack_bf16(__int2float_rn(a), __int2float_rn(b)); }
__device__ __forceinline__ void k_scale_split(uint32_t s, uint32_t& hi, uint32_t& lo) {
    const float f0 = __uint_as_float(s << 16) * SCALE_LOG2, f1 = __uint_as_float(s & 0xffff0000u) * SCALE_LOG2;
    hi = pack_bf16(f0, f1);
    lo = pack_bf16(f0 - __uint_as_float(hi << 16), f1 - __uint_as_float(hi & 0xffff0000u));
}
__device__ __forceinline__ uint32_t dq_k(int a, int b, uint32_t z, uint32_t hi, uint32_t lo) {
    const uint32_t t = bf2_sub(codes_bf2(a, b), z);
    return bf2_fma(t, hi, bf2_mul(t, lo));
}
__device__ __forceinline__ uint32_t dq_v(int a, int b, uint32_t z, uint32_t s) { return bf2_mul(bf2_sub(codes_bf2(a, b), z), s); }

__device__ __forceinline__ void ldg_stream2(int& a, int& b, const int* p, uint64_t pol) {
    asm volatile("ld.global.nc.L1::no_allocate.L2::cache_hint.v2.s32 {%0, %1}, [%2], %3;" : "=r"(a), "=r"(b) : "l"(p), "l"(pol));
}
__device__ __forceinline__ void ldg_stream4(int& a, int& b, int& c, int& d, const int* p, uint64_t pol) {
    asm volatile("ld.global.nc.L1::no_allocate.L2::cache_hint.v4.s32 {%0, %1, %2, %3}, [%4], %5;" : "=r"(a), "=r"(b), "=r"(c), "=r"(d) : "l"(p), "l"(pol));
}
__device__ __forceinline__ void dq_load(int (&v)[16], uint32_t (&zs)[4], const DqItem& d, int lane, const DqPtrs& g, uint64_t pol) {
    if (d.kv == 0) {
        const int* src = g.qk + (size_t)(d.head * SEQ + d.tok) * DH + 4 * lane;
#pragma unroll
        for (int r = 0; r < 4; r++) ldg_stream4(v[4 * r], v[4 * r + 1], v[4 * r + 2], v[4 * r + 3], src + r * DH, pol);
        const int so = (d.head * NGK + d.tok / GRP) * DH + 4 * lane;
        const uint2 zz = __ldg(reinterpret_cast<const uint2*>(g.kz + so)), ss = __ldg(reinterpret_cast<const uint2*>(g.ks + so));
        zs[0] = zz.x; zs[1] = zz.y; zs[2] = ss.x; zs[3] = ss.y;
    } else {
        const int tk = d.head * SEQ + d.tok + (lane >> 4);
        const int* src = g.qv + (size_t)tk * DH + 32 * ((lane & 15) >> 2) + 2 * (lane & 3);
        const unsigned short* z = reinterpret_cast<const unsigned short*>(g.vz) + tk;
        const unsigned short* sc = reinterpret_cast<const unsigned short*>(g.vs) + tk;
#pragma unroll
        for (int r = 0; r < 2; r++) {
#pragma unroll
            for (int c = 0; c < 4; c++) ldg_stream2(v[8 * r + 2 * c], v[8 * r + 2 * c + 1], src + 2 * r * DH + 8 * c, pol);
            zs[r] = __ldg(z + 2 * r); zs[2 + r] = __ldg(sc + 2 * r);
        }
    }
}
__device__ __forceinline__ void dq_convert_store(const int (&v)[16], const uint32_t (&zs)[4], const DqItem& d, int lane) {
    const int tr = d.tok % BN;
    uint8_t* tile = kv_tile(d.kv, d.head, d.tok / BN);
    if (d.kv == 0) {
        uint32_t h0, l0, h1, l1;
        k_scale_split(zs[2], h0, l0); k_scale_split(zs[3], h1, l1);
        uint8_t* dst = tile + (lane >> 4) * (TILE_BYTES / 2) + (lane & 1) * 8 + tr * 128;
        const int ch = (lane & 15) >> 1;
#pragma unroll
        for (int r = 0; r < 4; r++)
            *reinterpret_cast<uint2*>(dst + r * 128 + ((ch ^ ((tr + r) & 7)) << 4)) =
                make_uint2(dq_k(v[4 * r], v[4 * r + 1], zs[0], h0, l0), dq_k(v[4 * r + 2], v[4 * r + 3], zs[1], h1, l1));
    } else {
        const int i = (lane & 15) >> 2, ch = 4 * (i & 1) + (lane & 3), t0 = tr + (lane >> 4);
        uint8_t* dst = tile + (i >> 1) * (TILE_BYTES / 2) + t0 * 128;
#pragma unroll
        for (int r = 0; r < 2; r++) {
            const uint32_t z = zs[r] * 0x10001u, s = zs[2 + r] * 0x10001u;
            *reinterpret_cast<uint4*>(dst + 2 * r * 128 + ((ch ^ ((t0 + 2 * r) & 7)) << 4)) =
                make_uint4(dq_v(v[8 * r], v[8 * r + 1], z, s), dq_v(v[8 * r + 2], v[8 * r + 3], z, s),
                           dq_v(v[8 * r + 4], v[8 * r + 5], z, s), dq_v(v[8 * r + 6], v[8 * r + 7], z, s));
        }
    }
}
__device__ __forceinline__ void dq_signal(const DqItem& d, int lane) {
    asm volatile("fence.proxy.async.global;" ::: "memory");
    __syncwarp();
    if (lane == 0) asm volatile("red.release.gpu.global.add.u32 [%0], 1;" ::"l"(g_cnt + d.head * UNITS_PER_HEAD + d.p) : "memory");
}
__device__ __forceinline__ void dequant_loop(int it, int stride, int end, int h0, int h0inv, int lane, const DqPtrs& g, uint64_t pol) {
    if (it >= end) return;
    DqItem d = item_decode(it, h0, h0inv);
    int v[16]; uint32_t zs[4];
    dq_load(v, zs, d, lane, g, pol);
    while (true) {
        dq_convert_store(v, zs, d, lane);
        const DqItem dc = d;
        it += stride;
        const bool more = it < end;
        if (more) {
            d = item_decode(it, h0, h0inv);
            dq_load(v, zs, d, lane, g, pol);
        }
        dq_signal(dc, lane);
        if (!more) break;
    }
}
__device__ __forceinline__ void dq_bulk16(uint32_t src, uint32_t dst, uint32_t bar_free, const DqItem& d, int lane, const DqPtrs& g,
                                          uint32_t bar_ready, uint32_t parity) {
    uint32_t zs[16];
    if (d.kv == 0) {
        const int so = (d.head * NGK + d.tok / GRP) * DH + 4 * lane;
        const uint2 zz = __ldg(reinterpret_cast<const uint2*>(g.kz + so)), ss = __ldg(reinterpret_cast<const uint2*>(g.ks + so));
        zs[0] = zz.x; zs[1] = zz.y;
        k_scale_split(ss.x, zs[2], zs[3]); k_scale_split(ss.y, zs[4], zs[5]);
    } else {
        const uint4* z = reinterpret_cast<const uint4*>(g.vz + d.head * SEQ + d.tok);
        const uint4* s = reinterpret_cast<const uint4*>(g.vs + d.head * SEQ + d.tok);
        const uint4 z0 = __ldg(z), z1 = __ldg(z + 1), s0 = __ldg(s), s1 = __ldg(s + 1);
        zs[0] = z0.x; zs[1] = z0.y; zs[2] = z0.z; zs[3] = z0.w; zs[4] = z1.x; zs[5] = z1.y; zs[6] = z1.z; zs[7] = z1.w;
        zs[8] = s0.x; zs[9] = s0.y; zs[10] = s0.z; zs[11] = s0.w; zs[12] = s1.x; zs[13] = s1.y; zs[14] = s1.z; zs[15] = s1.w;
    }
    mbar_wait(bar_ready, parity);
    int v[64];
#pragma unroll
    for (int r = 0; r < 16; r++)
        asm volatile("ld.shared.v4.s32 {%0, %1, %2, %3}, [%4];" : "=r"(v[4 * r]), "=r"(v[4 * r + 1]), "=r"(v[4 * r + 2]), "=r"(v[4 * r + 3])
                     : "r"(src + r * 512 + lane * 16) : "memory");
    __syncwarp();
    if (lane == 0) {
        mbar_arrive(bar_free);
        asm volatile("cp.async.bulk.wait_group 0;" ::: "memory");
    }
    __syncwarp();
    if (d.kv == 0) {
        const uint32_t a = dst + (lane >> 4) * 2048 + (lane & 1) * 8;
        const int ch = (lane & 15) >> 1;
#pragma unroll
        for (int r = 0; r < 16; r++)
            asm volatile("st.shared.v2.u32 [%0], {%1, %2};" ::"r"(a + r * 128 + ((ch ^ (r & 7)) << 4)),
                         "r"(dq_k(v[4 * r], v[4 * r + 1], zs[0], zs[2], zs[3])), "r"(dq_k(v[4 * r + 2], v[4 * r + 3], zs[1], zs[4], zs[5])) : "memory");
    } else {
        const int i = lane >> 3, c = (lane & 7) >> 1, ch = 4 * (i & 1) + 2 * (lane & 1);
        const uint32_t a = dst + (i >> 1) * 2048 + 4 * c;
#pragma unroll
        for (int r = 0; r < 16; r++) {
            const uint32_t sel = (r & 1) ? 0x3232u : 0x1010u;
            const uint32_t z = __byte_perm(zs[r >> 1], 0, sel), s = __byte_perm(zs[8 + (r >> 1)], 0, sel);
            asm volatile("st.shared.u32 [%0], %1;" ::"r"(a + r * 128 + ((ch ^ (r & 7)) << 4)), "r"(dq_v(v[4 * r], v[4 * r + 1], z, s)) : "memory");
            asm volatile("st.shared.u32 [%0], %1;" ::"r"(a + r * 128 + (((ch + 1) ^ (r & 7)) << 4)), "r"(dq_v(v[4 * r + 2], v[4 * r + 3], z, s)) : "memory");
        }
    }
    asm volatile("fence.proxy.async.shared::cta;" ::: "memory");
    __syncwarp();
    if (lane == 0) {
        uint8_t* out = kv_tile(d.kv, d.head, d.tok / BN) + (d.tok % BN) * 128;
        bulk_store(out, dst, 2048);
        bulk_store(out + TILE_BYTES / 2, dst + 2048, 2048);
        asm volatile("cp.async.bulk.commit_group;" ::: "memory");
    }
}

template <int V> struct IC { static constexpr int value = V; };
struct Ring {
    uint32_t slot, phase;
    __device__ __forceinline__ void advance() { if (++slot == NS) { slot = 0; phase ^= 1; } }
};

__device__ __forceinline__ void load_q(uint32_t (&qf)[32], uint32_t qrow, uint32_t qsw) {
#pragma unroll
    for (int kk = 0; kk < 8; kk++)
        asm volatile("ldmatrix.sync.aligned.m8n8.x4.shared.b16 {%0, %1, %2, %3}, [%4];"
                     : "=r"(qf[4 * kk]), "=r"(qf[4 * kk + 1]), "=r"(qf[4 * kk + 2]), "=r"(qf[4 * kk + 3])
                     : "r"(qrow + (kk >> 2) * (QBUF_BYTES / 2) + (qsw ^ ((kk & 3) << 5))) : "memory");
}
__device__ __forceinline__ void issue_qk(float (&S)[64], const uint32_t (&qf)[32], uint32_t kaddr) {
    const uint64_t hi = (uint64_t)(64u | (1u << 30)) << 32;
    const uint32_t lo = ((kaddr & 0x3FFFFu) >> 4) | (1u << 16);
#pragma unroll
    for (int kk = 0; kk < 8; kk++)
        wgmma_rs<0>(S, qf[4 * kk], qf[4 * kk + 1], qf[4 * kk + 2], qf[4 * kk + 3],
                    hi | (uint64_t)(lo + (kk >> 2) * 1024 + (kk & 3) * 2), kk != 0);
}
__device__ __forceinline__ void issue_pv(float (&O)[64], const uint32_t (&P)[32], uint32_t vaddr, int acc) {
    const uint64_t hi = (uint64_t)(64u | (1u << 30)) << 32;
    const uint32_t lo = ((vaddr & 0x3FFFFu) >> 4) | (1024u << 16);
#pragma unroll
    for (int kk = 0; kk < 8; kk++)
        wgmma_rs<1>(O, P[4 * kk], P[4 * kk + 1], P[4 * kk + 2], P[4 * kk + 3], hi | (uint64_t)(lo + kk * 128), kk != 0 ? 1 : acc);
}
template <int J0, int J1>
__device__ __forceinline__ void exp_part(float (&S)[64], float (&acc)[4]) {
#pragma unroll
    for (int j = J0; j < J1; j++) {
        S[4 * j + 0] = ex2(S[4 * j + 0]);
        S[4 * j + 1] = ex2(S[4 * j + 1]);
        S[4 * j + 2] = ex2(S[4 * j + 2]);
        S[4 * j + 3] = ex2(S[4 * j + 3]);
        if (j == 0) { acc[0] = S[0]; acc[1] = S[1]; acc[2] = S[2]; acc[3] = S[3]; }
        else { acc[0] += S[4 * j + 0]; acc[1] += S[4 * j + 1]; acc[2] += S[4 * j + 2]; acc[3] += S[4 * j + 3]; }
    }
}
__device__ __forceinline__ void cvt_p(const float (&S)[64], uint32_t (&P)[32]) {
#pragma unroll
    for (int j = 0; j < 16; j++) {
        P[2 * j] = pack_bf16(S[4 * j], S[4 * j + 1]);
        P[2 * j + 1] = pack_bf16(S[4 * j + 2], S[4 * j + 3]);
    }
}
__device__ __forceinline__ bool store_o(const float (&O)[64], float l0, float l1, __nv_bfloat16* __restrict__ orow) {
    l0 += __shfl_xor_sync(0xffffffffu, l0, 1); l1 += __shfl_xor_sync(0xffffffffu, l1, 1);
    l0 += __shfl_xor_sync(0xffffffffu, l0, 2); l1 += __shfl_xor_sync(0xffffffffu, l1, 2);
    const float i0 = __fdividef(1.0f, l0), i1 = __fdividef(1.0f, l1);
    float c0 = 0.f, c1 = 0.f, c2 = 0.f, c3 = 0.f;
#pragma unroll
    for (int i = 0; i < 4; i++) {
        uint4 a, b;
        a.x = pack_bf16(O[16 * i + 0] * i0, O[16 * i + 1] * i0);
        a.y = pack_bf16(O[16 * i + 4] * i0, O[16 * i + 5] * i0);
        a.z = pack_bf16(O[16 * i + 8] * i0, O[16 * i + 9] * i0);
        a.w = pack_bf16(O[16 * i + 12] * i0, O[16 * i + 13] * i0);
        b.x = pack_bf16(O[16 * i + 2] * i1, O[16 * i + 3] * i1);
        b.y = pack_bf16(O[16 * i + 6] * i1, O[16 * i + 7] * i1);
        b.z = pack_bf16(O[16 * i + 10] * i1, O[16 * i + 11] * i1);
        b.w = pack_bf16(O[16 * i + 14] * i1, O[16 * i + 15] * i1);
        *reinterpret_cast<uint4*>(orow + 32 * i) = a;
        *reinterpret_cast<uint4*>(orow + 8 * DH + 32 * i) = b;
#pragma unroll
        for (int e = 0; e < 16; e += 4) {
            c0 = fmaf(O[16 * i + e], 0.f, c0); c1 = fmaf(O[16 * i + e + 1], 0.f, c1);
            c2 = fmaf(O[16 * i + e + 2], 0.f, c2); c3 = fmaf(O[16 * i + e + 3], 0.f, c3);
        }
    }
    return l0 >= L_MIN && l0 <= L_MAX && l1 >= L_MIN && l1 <= L_MAX && (c0 + c1) + (c2 + c3) == 0.f;
}

__global__ void __cluster_dims__(2, 1, 1) __launch_bounds__(384, 1)
attn_kernel(const __grid_constant__ CUtensorMap qmap, const int* __restrict__ qk, const int* __restrict__ qv,
            const __nv_bfloat16* __restrict__ ks, const __nv_bfloat16* __restrict__ kz,
            const __nv_bfloat16* __restrict__ vs, const __nv_bfloat16* __restrict__ vz,
            __nv_bfloat16* __restrict__ out) {
    extern __shared__ __align__(1024) uint8_t smem_raw[];
    const uint32_t sb = smem_u32(smem_raw);
    const uint32_t qbuf = sb + NS * TILE_BYTES;
    const uint32_t bar_full = qbuf + QBUF_BYTES, bar_empty = bar_full + 8 * NS;
    const uint32_t bar_qfull = bar_empty + 8 * NS, bar_qempty = bar_qfull + 8, pin_addr = bar_qempty + 8;
    const uint32_t bar_bfull = pin_addr + 8, bar_bempty = bar_bfull + 8 * NIN;
    const uint32_t bar_rfull = bar_bempty + 8 * NIN, bar_rempty = bar_rfull + 16;
    volatile uint8_t* redo = smem_raw + NS * TILE_BYTES + QBUF_BYTES + 512;
    const int wg = __shfl_sync(0xffffffffu, threadIdx.x >> 7, 0);
    const int warp = __shfl_sync(0xffffffffu, (threadIdx.x >> 5) & 3, 0);
    const int lane = threadIdx.x & 31;
    uint32_t rank; asm("mov.u32 %0, %%cluster_ctarank;" : "=r"(rank));
    const int cluster_id = blockIdx.x >> 1, nclusters = gridDim.x >> 1;

    DBG_STAMP(0);
    const int rem = NTILES % nclusters;
    const int nlight = rem ? nclusters - rem : 0;
    const bool bulk = nlight >= 6;
    const bool light = bulk && cluster_id >= rem;
    const int h0 = min(HKV, ((bulk ? rem : nclusters) + TILES_PER_HEAD - 1) / TILES_PER_HEAD);
    const int h0inv = (65536 + h0 - 1) / h0;
    const int nfirst = min(NITEMS, (int)((bulk ? 2 * rem : gridDim.x) * 11) & ~(ITEMS_PER_CHUNK - 1));
    const int chunk0 = nfirst / ITEMS_PER_CHUNK + (int)blockIdx.x - 2 * rem, chunk_stride = 2 * nlight;
    const DqPtrs dq{qk, qv, ks, kz, vs, vz};
    uint64_t pol;
    asm volatile("createpolicy.fractional.L2::evict_first.b64 %0, 1.0;" : "=l"(pol));
    const int gwarp = wg * 4 + warp;

    if (gwarp != 0) {
        cluster_arrive();
        if (!light) dequant_loop(blockIdx.x * 11 + gwarp - 1, NITEMS, nfirst, h0, h0inv, lane, dq, pol);
        cluster_wait();
        if (light) {
            const uint32_t obuf = sb + NIN * TILE_BYTES + (gwarp - 1) * 4096;
            int pend0 = -1, pend1 = -1, pend2 = -1, inflight = -1, npend = 0;
            auto flush = [&]() {
                if (lane == 0) {
                    asm volatile("fence.acq_rel.gpu;" ::: "memory");
                    if (pend0 >= 0) asm volatile("red.relaxed.gpu.global.add.u32 [%0], 4;" ::"l"(g_cnt + pend0) : "memory");
                    if (pend1 >= 0) asm volatile("red.relaxed.gpu.global.add.u32 [%0], 4;" ::"l"(g_cnt + pend1) : "memory");
                    if (pend2 >= 0) asm volatile("red.relaxed.gpu.global.add.u32 [%0], 4;" ::"l"(g_cnt + pend2) : "memory");
                }
                pend0 = pend1 = pend2 = -1; npend = 0;
            };
            for (int j = gwarp - 1;; j += 11) {
                const int k = j >> 2, c = chunk0 + k * chunk_stride;
                if (c >= NCHUNKS) break;
                const DqItem d = item_decode(c * ITEMS_PER_CHUNK + (j & 3) * 4, h0, h0inv);
                const int slot = k % NIN;
                dq_bulk16(sb + slot * TILE_BYTES + (j & 3) * 8192, obuf, bar_bempty + 8 * slot, d, lane, dq, bar_bfull + 8 * slot, (k / NIN) & 1);
                if (inflight >= 0) { pend2 = pend1; pend1 = pend0; pend0 = inflight; if (++npend == FLUSH_N) flush(); }
                inflight = d.head * UNITS_PER_HEAD + d.p;
            }
            if (inflight >= 0) {
                if (lane == 0) asm volatile("cp.async.bulk.wait_group 0;" ::: "memory");
                pend2 = pend1; pend1 = pend0; pend0 = inflight;
                flush();
            }
            __syncwarp();
        }
    } else {
        if (lane == 0) {
            if (sb & 1023u) __trap();
            for (int s = 0; s < NS; s++) { mbar_init(bar_full + 8 * s, 1); mbar_init(bar_empty + 8 * s, 4); }
            mbar_init(bar_qfull, 1); mbar_init(bar_qempty, 8);
            for (int s = 0; s < NIN; s++) { mbar_init(bar_bfull + 8 * s, 1); mbar_init(bar_bempty + 8 * s, 4); }
            for (int s = 0; s < 2; s++) { mbar_init(bar_rfull + 8 * s, 1); mbar_init(bar_rempty + 8 * s, 2); }
            asm volatile("fence.mbarrier_init.release.cluster;" ::: "memory");
            mbar_expect_tx(bar_qfull, QBUF_BYTES);
            tma_load_2d(qbuf, &qmap, 0, cluster_id * 256 + rank * 128, bar_qfull);
            tma_load_2d(qbuf + QBUF_BYTES / 2, &qmap, 64, cluster_id * 256 + rank * 128, bar_qfull);
        }
        reinterpret_cast<volatile uint32_t*>(redo)[lane] = 0;
        reinterpret_cast<volatile uint32_t*>(redo)[lane + 32] = 0;
        __syncwarp();
        cluster_arrive_release();
        if (light && lane == 0) {
            int k = 0;
            for (int c = chunk0; c < NCHUNKS; c += chunk_stride, k++) {
                const int slot = k % NIN;
                const DqItem d = item_decode(c * ITEMS_PER_CHUNK, h0, h0inv);
                mbar_wait(bar_bempty + 8 * slot, ((k / NIN) & 1) ^ 1);
                mbar_expect_tx(bar_bfull + 8 * slot, TILE_BYTES);
                bulk_load_hint(sb + slot * TILE_BYTES, (d.kv ? qv : qk) + (size_t)(d.head * SEQ + d.tok) * DH, TILE_BYTES, bar_bfull + 8 * slot, pol);
            }
        }
        __syncwarp();
        cluster_wait();
    }
    if (light) { cluster_arrive_release(); cluster_wait(); }

    if (wg == 0) {
        asm volatile("setmaxnreg.dec.sync.aligned.u32 56;");
        if (warp == 0) {
            uint32_t qphase = 0;
            auto load_qtile = [&](int t) {
                if (lane == 0) {
                    mbar_wait(bar_qempty, qphase);
                    mbar_expect_tx(bar_qfull, QBUF_BYTES);
                    tma_load_2d(qbuf, &qmap, 0, t * 256 + rank * 128, bar_qfull);
                    tma_load_2d(qbuf + QBUF_BYTES / 2, &qmap, 64, t * 256 + rank * 128, bar_qfull);
                }
                __syncwarp();
                qphase ^= 1;
            };
            Ring r{0, 1};
            int vhead = -1;
            uint32_t vmask = 0;
            auto load = [&](int kv, int head, int blk) {
                const int p = kv == 0 ? (blk == 0 ? 0 : 2 * blk - 1) : (blk == NBLK - 1 ? UNITS_PER_HEAD - 1 : 2 * blk + 2);
                if (head != vhead) { vhead = head; vmask = 0; }
                if (!((vmask >> p) & 1)) {
                    uint32_t n = 0;
                    while (true) {
                        unsigned int c;
                        asm volatile("ld.acquire.gpu.global.u32 %0, [%1];" : "=r"(c) : "l"(g_cnt + head * UNITS_PER_HEAD + lane) : "memory");
                        vmask = __ballot_sync(0xffffffffu, c == ITEMS_PER_UNIT);
                        if ((vmask >> p) & 1) break;
                        if (++n > (1u << 22)) __trap();
                    }
                    asm volatile("fence.proxy.async.global;" ::: "memory");
                }
                if (lane == 0) {
                    mbar_wait(bar_empty + 8 * r.slot, r.phase);
                    mbar_expect_tx(bar_full + 8 * r.slot, TILE_BYTES);
                    bulk_load_mc(sb + r.slot * TILE_BYTES + rank * (TILE_BYTES / 2), kv_tile(kv, head, blk) + rank * (TILE_BYTES / 2),
                                 TILE_BYTES / 2, bar_full + 8 * r.slot, (uint16_t)3);
                }
                __syncwarp();
                r.advance();
            };
            load(0, cluster_id / TILES_PER_HEAD, 0);
            for (int t = cluster_id; t < NTILES; t += nclusters) {
                const int head = t / TILES_PER_HEAD;
                const int tn = t + nclusters;
                for (int j = 0; j < NBLK; j++) {
                    if (j == 4 && tn < NTILES) load_qtile(tn);
                    if (j < NBLK - 1) load(0, head, j + 1);
                    else if (tn < NTILES) load(0, tn / TILES_PER_HEAD, 0);
                    load(1, head, j);
                }
            }
            if (lane == 0) {
                const unsigned int prev = atomicAdd(&g_done, 1u);
                if (prev == gridDim.x - 1) {
                    for (int i = 0; i < HKV * UNITS_PER_HEAD; i++) g_cnt[i] = 0;
                    g_done = 0;
                }
            }
            __syncwarp();
            bar_sync(3, 288);
            uint32_t n = 0;
            for (int t = cluster_id, k = 0; t < NTILES; t += nclusters, k++) {
                if (!redo[k]) continue;
                load_qtile(t);
                if (lane == 0) {
                    for (int j = 0; j < 2 * NBLK; j++, n++) {
                        const uint32_t s = n & 1;
                        mbar_wait(bar_rempty + 8 * s, ((n >> 1) & 1) ^ 1);
                        mbar_expect_tx(bar_rfull + 8 * s, TILE_BYTES);
                        bulk_load(sb + s * TILE_BYTES, kv_tile(j & 1, t / TILES_PER_HEAD, j >> 1), TILE_BYTES, bar_rfull + 8 * s);
                    }
                }
                __syncwarp();
            }
        } else {
            if (!bulk) dequant_loop(nfirst + blockIdx.x * 3 + (warp - 1), gridDim.x * 3, NITEMS, h0, h0inv, lane, dq, pol);
        }
        cluster_arrive(); cluster_wait();
    } else {
        asm volatile("setmaxnreg.inc.sync.aligned.u32 224;");
        const int w = wg - 1;
        const int my_bar = 1 + w, other_bar = 2 - w;
        const int row_in_tile = rank * 128 + w * 64 + warp * 16 + (lane >> 2);
        const int coff = (lane & 3) * 8;
        const uint32_t qrow = qbuf + (w * 64 + warp * 16 + (lane & 15)) * 128;
        const uint32_t qsw = ((lane >> 4) ^ (lane & 7)) << 4;
        const uint32_t rem_empty = mapa(bar_empty, warp & 1);
        const bool releaser = lane == 0 && warp < 2;
        uint32_t qf[32], P[32];
        float S[64], O[64];
        float l0 = 0.f, l1 = 0.f, lo0 = 1.f, lo1 = 1.f;
        uint32_t qphase = 0;
        Ring r{0, 0};
        auto release = [&]() {
            if (releaser) mbar_arrive_remote(rem_empty + 8 * r.slot);
            r.advance();
        };
        auto reload_q = [&]() {
            mbar_wait(bar_qfull, qphase);
            qphase ^= 1;
            load_q(qf, qrow, qsw);
            __syncwarp();
            if (lane == 0) mbar_arrive(bar_qempty);
        };
        auto pin = [&](float x) {
            asm volatile("{\n.reg .pred p;\nsetp.eq.f32 p, %0, 0fBF800000;\n@p st.shared.f32 [%1], %0;\n}\n" ::"f"(x), "r"(pin_addr) : "memory");
        };
        int t = cluster_id, tk = 0;
#pragma unroll
        for (int i = 0; i < 64; i++) { S[i] = 0.f; O[i] = 0.f; }
        DBG_IT(0);
        if (w == 1) bar_arrive(1, 256);
        reload_q();
        {
            mbar_wait(bar_full + 8 * r.slot, r.phase);
            bar_sync(my_bar, 256);
            wg_fence();
            issue_qk(S, qf, sb + r.slot * TILE_BYTES);
            wg_commit();
            bar_arrive(other_bar, 256);
            wg_wait<0>();
            fence_regs(S);
            release();
            float acc[4];
            exp_part<0, 16>(S, acc);
            l0 = acc[0] + acc[1]; l1 = acc[2] + acc[3];
            cvt_p(S, P);
        }
        uint32_t ready = 0;
        auto step = [&](auto first, bool store_prev, __nv_bfloat16* orow, bool swap_l, bool new_q) {
            constexpr bool FIRST = decltype(first)::value;
            const uint32_t kslot = r.slot;
            Ring rv = r; rv.advance();
            if (!ready) {
                mbar_wait(bar_full + 8 * r.slot, r.phase);
                mbar_wait(bar_full + 8 * rv.slot, rv.phase);
            }
            bar_sync(my_bar, 256);
            wg_fence();
            issue_qk(S, qf, sb + kslot * TILE_BYTES);
            wg_commit();
            if (FIRST) {
                if (store_prev) { if (!store_o(O, lo0, lo1, orow)) redo[tk - 1] = 1; }
                fence_regs(O);
                wg_fence();
            }
            issue_pv(O, P, sb + rv.slot * TILE_BYTES, !FIRST);
            wg_commit();
            bar_arrive(other_bar, 256);
            wg_wait<1>();
            fence_regs(S);
            release();
            if (!FIRST && new_q) { fence_regs(qf); reload_q(); }
            float acc[4];
            exp_part<0, PIN_J>(S, acc);
            pin((acc[0] + acc[1]) + (acc[2] + acc[3]));
            wg_wait<0>();
            fence_regs(O);
            fence_regs(P);
            release();
            {
                Ring rn = r; rn.advance();
                ready = mbar_test(bar_full + 8 * r.slot, r.phase) & mbar_test(bar_full + 8 * rn.slot, rn.phase);
            }
            exp_part<PIN_J, 16>(S, acc);
            cvt_p(S, P);
            if (!FIRST && swap_l) { lo0 = l0; lo1 = l1; l0 = 0.f; l1 = 0.f; }
            l0 += acc[0] + acc[1]; l1 += acc[2] + acc[3];
        };
        DBG_STAMP(1);
        __nv_bfloat16* oprev = out;
        while (true) {
            const int tn = t + nclusters;
            const bool has_next = tn < NTILES;
            step(IC<1>{}, tk > 0, oprev, false, false);
            const int jend = has_next ? NBLK : NBLK - 1;
#pragma unroll 1
            for (int j = 1; j < jend; j++) step(IC<0>{}, false, nullptr, j == NBLK - 1, has_next && j == NBLK - 2);
            oprev = out + (size_t)(t * 256 + row_in_tile) * DH + coff;
            if (has_next) {
                t = tn; tk++;
            } else {
                mbar_wait(bar_full + 8 * r.slot, r.phase);
                bar_sync(my_bar, 256);
                wg_fence();
                issue_pv(O, P, sb + r.slot * TILE_BYTES, 1);
                wg_commit();
                if (w == 0) bar_arrive(other_bar, 256);
                wg_wait<0>();
                fence_regs(O);
                release();
                if (!store_o(O, l0, l1, oprev)) redo[tk] = 1;
                break;
            }
        }
        bar_sync(3, 288);
        uint32_t n = 0;
        for (int tt = cluster_id, k = 0; tt < NTILES; tt += nclusters, k++) {
            if (!redo[k]) continue;
            mbar_wait(bar_qfull, qphase);
            qphase ^= 1;
            float m0 = -INFINITY, m1 = -INFINITY;
            l0 = 0.f; l1 = 0.f;
#pragma unroll 1
            for (int j = 0; j < NBLK; j++) {
                load_q(qf, qrow, qsw);
                mbar_wait(bar_rfull + 8 * (n & 1), (n >> 1) & 1);
                wg_fence();
                issue_qk(S, qf, sb + (n & 1) * TILE_BYTES);
                wg_commit();
                wg_wait<0>();
                fence_regs(S);
                if (warp == 0 && lane == 0) mbar_arrive(bar_rempty + 8 * (n & 1));
                n++;
                float a0 = m0, a1 = m1;
#pragma unroll
                for (int i = 0; i < 16; i++) {
                    a0 = fmaxf(a0, fmaxf(S[4 * i], S[4 * i + 1]));
                    a1 = fmaxf(a1, fmaxf(S[4 * i + 2], S[4 * i + 3]));
                }
                a0 = fmaxf(a0, __shfl_xor_sync(0xffffffffu, a0, 1)); a1 = fmaxf(a1, __shfl_xor_sync(0xffffffffu, a1, 1));
                a0 = fmaxf(a0, __shfl_xor_sync(0xffffffffu, a0, 2)); a1 = fmaxf(a1, __shfl_xor_sync(0xffffffffu, a1, 2));
                const float al0 = ex2(m0 - a0), al1 = ex2(m1 - a1);
                m0 = a0; m1 = a1;
#pragma unroll
                for (int i = 0; i < 16; i++) {
                    S[4 * i] -= a0; S[4 * i + 1] -= a0; S[4 * i + 2] -= a1; S[4 * i + 3] -= a1;
                    O[4 * i] *= al0; O[4 * i + 1] *= al0; O[4 * i + 2] *= al1; O[4 * i + 3] *= al1;
                }
                float acc[4];
                exp_part<0, 16>(S, acc);
                l0 = l0 * al0 + (acc[0] + acc[1]); l1 = l1 * al1 + (acc[2] + acc[3]);
                cvt_p(S, P);
                mbar_wait(bar_rfull + 8 * (n & 1), (n >> 1) & 1);
                wg_fence();
                issue_pv(O, P, sb + (n & 1) * TILE_BYTES, j != 0);
                wg_commit();
                wg_wait<0>();
                fence_regs(O);
                if (warp == 0 && lane == 0) mbar_arrive(bar_rempty + 8 * (n & 1));
                n++;
            }
            __syncwarp();
            if (lane == 0) mbar_arrive(bar_qempty);
            store_o(O, l0, l1, out + (size_t)(tt * 256 + row_in_tile) * DH + coff);
        }
        cluster_arrive(); cluster_wait();
    }
}

}

extern "C" void kernel_launch(void* const* d_in, const int* in_sizes, int n_in, void* d_out, int out_size) {
    const __nv_bfloat16* q = (const __nv_bfloat16*)d_in[0];
    const int* qk = (const int*)d_in[1];
    const int* qv = (const int*)d_in[2];
    const __nv_bfloat16* ks = (const __nv_bfloat16*)d_in[3];
    const __nv_bfloat16* kz = (const __nv_bfloat16*)d_in[4];
    const __nv_bfloat16* vs = (const __nv_bfloat16*)d_in[5];
    const __nv_bfloat16* vz = (const __nv_bfloat16*)d_in[6];
    typedef CUresult (*EncodeFn)(CUtensorMap*, CUtensorMapDataType, cuuint32_t, void*, const cuuint64_t*, const cuuint64_t*,
                                 const cuuint32_t*, const cuuint32_t*, CUtensorMapInterleave, CUtensorMapSwizzle,
                                 CUtensorMapL2promotion, CUtensorMapFloatOOBfill);
    static EncodeFn encode = nullptr;
    static int grid = 0;
    if (grid == 0) {
        void* fn = nullptr;
        cudaDriverEntryPointQueryResult qr;
        cudaGetDriverEntryPoint("cuTensorMapEncodeTiled", &fn, cudaEnableDefault, &qr);
        encode = (EncodeFn)fn;
        cudaFuncSetAttribute(attn_kernel, cudaFuncAttributeMaxDynamicSharedMemorySize, SMEM_BYTES);
        cudaLaunchConfig_t cfg = {};
        cfg.gridDim = dim3(2, 1, 1); cfg.blockDim = dim3(384, 1, 1); cfg.dynamicSmemBytes = SMEM_BYTES;
        cudaLaunchAttribute at[1];
        at[0].id = cudaLaunchAttributeClusterDimension;
        at[0].val.clusterDim.x = 2; at[0].val.clusterDim.y = 1; at[0].val.clusterDim.z = 1;
        cfg.attrs = at; cfg.numAttrs = 1;
        int nc = 0;
        if (cudaOccupancyMaxActiveClusters(&nc, attn_kernel, &cfg) != cudaSuccess || nc <= 0) { nc = 1; (void)cudaGetLastError(); }
        if (nc > NTILES) nc = NTILES;
        if (FORCE_CLUSTERS) nc = FORCE_CLUSTERS;
        grid = nc * 2;
    }
    CUtensorMap qmap;
    const cuuint64_t dims[2] = {(cuuint64_t)DH, (cuuint64_t)HQ * SEQ};
    const cuuint64_t strides[1] = {(cuuint64_t)DH * 2};
    const cuuint32_t box[2] = {64, 128};
    const cuuint32_t estr[2] = {1, 1};
    encode(&qmap, CU_TENSOR_MAP_DATA_TYPE_BFLOAT16, 2, (void*)q, dims, strides, box, estr, CU_TENSOR_MAP_INTERLEAVE_NONE,
           CU_TENSOR_MAP_SWIZZLE_128B, CU_TENSOR_MAP_L2_PROMOTION_L2_128B, CU_TENSOR_MAP_FLOAT_OOB_FILL_NONE);
    attn_kernel<<<grid, 384, SMEM_BYTES>>>(qmap, qk, qv, ks, kz, vs, vz, (__nv_bfloat16*)d_out);
}
```

```cpp
#include <cuda_runtime.h>
#include <cuda_bf16.h>
#include <cuda.h>
#include <stdint.h>

#define PIN_J 7
#define PFD 0
#define NFIRST 1
#define FORCE_CLUSTERS 0

namespace {

constexpr int HQ = 32, HKV = 8, SEQ = 2048, DH = 128, NGK = 2, GRP = SEQ / NGK;
constexpr int BN = 128, NBLK = SEQ / BN;
constexpr int TILE_BYTES = BN * DH * 2;
constexpr int NS = 6;
constexpr int NTILES = HQ * SEQ / 256;
constexpr int TILES_PER_HEAD = NTILES / HKV;
constexpr int QBUF_BYTES = 128 * DH * 2;
constexpr int SMEM_BYTES = NS * TILE_BYTES + QBUF_BYTES + 2048;
constexpr int UNITS_PER_HEAD = 2 * NBLK;
constexpr int ITEMS_PER_UNIT = 32;
constexpr int NITEMS = HKV * UNITS_PER_HEAD * ITEMS_PER_UNIT;
constexpr int ITEMS_PER_CHUNK = 16;
constexpr int NCHUNKS = NITEMS / ITEMS_PER_CHUNK;
constexpr int MIN_LIGHT = 6;
constexpr int MAX_CHUNKS_PER_CTA = (NCHUNKS + 2 * MIN_LIGHT - 1) / (2 * MIN_LIGHT);
constexpr int NIN = 4;
constexpr float SCALE_LOG2 = 0.08838834764831845f * 1.4426950408889634f;
constexpr float L_MIN = 9.094947017729282e-13f, L_MAX = 1099511627776.0f;

__device__ __align__(1024) uint4 g_kv[2 * HKV * NBLK * (TILE_BYTES / 16)];
__device__ __align__(128) unsigned int g_cnt[HKV * UNITS_PER_HEAD];
__device__ unsigned int g_done;

#define DBG_IT(i)
#define DBG_STAMP(i)
#define DBG_T(k)
#define DBG_S(k)

__device__ __forceinline__ uint32_t smem_u32(const void* p) { return (uint32_t)__cvta_generic_to_shared(p); }

__device__ __forceinline__ void mbar_init(uint32_t a, uint32_t cnt) {
    asm volatile("mbarrier.init.shared::cta.b64 [%0], %1;" ::"r"(a), "r"(cnt) : "memory");
}
__device__ __forceinline__ void mbar_expect_tx(uint32_t a, uint32_t bytes) {
    asm volatile("mbarrier.arrive.expect_tx.shared::cta.b64 _, [%0], %1;" ::"r"(a), "r"(bytes) : "memory");
}
__device__ __forceinline__ void mbar_wait(uint32_t a, uint32_t parity) {
    asm volatile(
        "{\n"
        ".reg .pred p;\n"
        ".reg .u32 n;\n"
        "mbarrier.try_wait.parity.shared::cta.b64 p, [%0], %1;\n"
        "@p bra WAIT_DONE;\n"
        "mov.u32 n, 0;\n"
        "WAIT_LOOP:\n"
        "mbarrier.try_wait.parity.shared::cta.b64 p, [%0], %1;\n"
        "@p bra WAIT_DONE;\n"
        "add.u32 n, n, 1;\n"
        "setp.lt.u32 p, n, 0x1000000;\n"
        "@p bra WAIT_LOOP;\n"
        "trap;\n"
        "WAIT_DONE:\n"
        "}\n" ::"r"(a), "r"(parity) : "memory");
}
__device__ __forceinline__ uint32_t mbar_test(uint32_t a, uint32_t parity) {
    uint32_t ok;
    asm volatile("{\n.reg .pred p;\nmbarrier.test_wait.parity.shared::cta.b64 p, [%1], %2;\nselp.u32 %0, 1, 0, p;\n}\n"
                 : "=r"(ok) : "r"(a), "r"(parity) : "memory");
    return ok;
}
__device__ __forceinline__ void mbar_arrive(uint32_t a) {
    asm volatile("mbarrier.arrive.shared::cta.b64 _, [%0];" ::"r"(a) : "memory");
}
__device__ __forceinline__ uint32_t mapa(uint32_t a, uint32_t cta) {
    uint32_t r; asm("mapa.shared::cluster.u32 %0, %1, %2;" : "=r"(r) : "r"(a), "r"(cta)); return r;
}
__device__ __forceinline__ void mbar_arrive_remote(uint32_t ra) {
    asm volatile("mbarrier.arrive.shared::cluster.b64 _, [%0];" ::"r"(ra) : "memory");
}
__device__ __forceinline__ void bulk_load(uint32_t dst, const void* src, uint32_t bytes, uint32_t bar) {
    asm volatile("cp.async.bulk.shared::cluster.global.mbarrier::complete_tx::bytes [%0], [%1], %2, [%3];"
        ::"r"(dst), "l"(src), "r"(bytes), "r"(bar) : "memory");
}
__device__ __forceinline__ void bulk_load_hint(uint32_t dst, const void* src, uint32_t bytes, uint32_t bar, uint64_t pol) {
    asm volatile("cp.async.bulk.shared::cluster.global.mbarrier::complete_tx::bytes.L2::cache_hint [%0], [%1], %2, [%3], %4;"
        ::"r"(dst), "l"(src), "r"(bytes), "r"(bar), "l"(pol) : "memory");
}
__device__ __forceinline__ void bulk_load_mc(uint32_t dst, const void* src, uint32_t bytes, uint32_t bar, uint16_t mask) {
    asm volatile("cp.async.bulk.shared::cluster.global.mbarrier::complete_tx::bytes.multicast::cluster [%0], [%1], %2, [%3], %4;"
        ::"r"(dst), "l"(src), "r"(bytes), "r"(bar), "h"(mask) : "memory");
}
__device__ __forceinline__ void bulk_store(void* dst, uint32_t src, uint32_t bytes) {
    asm volatile("cp.async.bulk.global.shared::cta.bulk_group [%0], [%1], %2;" ::"l"(dst), "r"(src), "r"(bytes) : "memory");
}
__device__ __forceinline__ void tma_load_2d(uint32_t dst, const CUtensorMap* map, int c0, int c1, uint32_t bar) {
    asm volatile("cp.async.bulk.tensor.2d.shared::cluster.global.mbarrier::complete_tx::bytes [%0], [%1, {%3, %4}], [%2];"
        ::"r"(dst), "l"(map), "r"(bar), "r"(c0), "r"(c1) : "memory");
}
__device__ __forceinline__ void cluster_arrive() { asm volatile("barrier.cluster.arrive.relaxed.aligned;" ::: "memory"); }
__device__ __forceinline__ void cluster_arrive_release() { asm volatile("barrier.cluster.arrive.release.aligned;" ::: "memory"); }
__device__ __forceinline__ void cluster_wait() { asm volatile("barrier.cluster.wait.aligned;" ::: "memory"); }
__device__ __forceinline__ void wg_fence() { asm volatile("wgmma.fence.sync.aligned;" ::: "memory"); }
__device__ __forceinline__ void wg_commit() { asm volatile("wgmma.commit_group.sync.aligned;" ::: "memory"); }
template <int N> __device__ __forceinline__ void wg_wait() { asm volatile("wgmma.wait_group.sync.aligned %0;" ::"n"(N) : "memory"); }
__device__ __forceinline__ void bar_sync(int id, int n) { asm volatile("bar.sync %0, %1;" ::"r"(id), "r"(n) : "memory"); }
__device__ __forceinline__ void bar_arrive(int id, int n) { asm volatile("bar.arrive %0, %1;" ::"r"(id), "r"(n) : "memory"); }

__device__ __forceinline__ float ex2(float x) { float y; asm("ex2.approx.ftz.f32 %0, %1;" : "=f"(y) : "f"(x)); return y; }
__device__ __forceinline__ uint32_t pack_bf16(float lo, float hi) {
    uint32_t r; asm("cvt.rn.bf16x2.f32 %0, %1, %2;" : "=r"(r) : "f"(hi), "f"(lo)); return r;
}
__device__ __forceinline__ uint32_t bf2_sub(uint32_t a, uint32_t b) { uint32_t r; asm("sub.rn.bf16x2 %0, %1, %2;" : "=r"(r) : "r"(a), "r"(b)); return r; }
__device__ __forceinline__ uint32_t bf2_mul(uint32_t a, uint32_t b) { uint32_t r; asm("mul.rn.bf16x2 %0, %1, %2;" : "=r"(r) : "r"(a), "r"(b)); return r; }
__device__ __forceinline__ uint32_t bf2_fma(uint32_t a, uint32_t b, uint32_t c) { uint32_t r; asm("fma.rn.bf16x2 %0, %1, %2, %3;" : "=r"(r) : "r"(a), "r"(b), "r"(c)); return r; }

#define F8(a, i) "+f"(a[i]), "+f"(a[i + 1]), "+f"(a[i + 2]), "+f"(a[i + 3]), "+f"(a[i + 4]), "+f"(a[i + 5]), "+f"(a[i + 6]), "+f"(a[i + 7])
#define F64(a) F8(a, 0), F8(a, 8), F8(a, 16), F8(a, 24), F8(a, 32), F8(a, 40), F8(a, 48), F8(a, 56)

template <int TB>
__device__ __forceinline__ void wgmma_rs(float (&d)[64], uint32_t a0, uint32_t a1, uint32_t a2, uint32_t a3, uint64_t desc, int scale_d) {
    asm volatile(
        "{\n.reg .pred p;\nsetp.ne.b32 p, %69, 0;\n"
        "wgmma.mma_async.sync.aligned.m64n128k16.f32.bf16.bf16 "
        "{%0,%1,%2,%3,%4,%5,%6,%7,%8,%9,%10,%11,%12,%13,%14,%15,"
        "%16,%17,%18,%19,%20,%21,%22,%23,%24,%25,%26,%27,%28,%29,%30,%31,"
        "%32,%33,%34,%35,%36,%37,%38,%39,%40,%41,%42,%43,%44,%45,%46,%47,"
        "%48,%49,%50,%51,%52,%53,%54,%55,%56,%57,%58,%59,%60,%61,%62,%63},"
        "{%64,%65,%66,%67}, %68, p, 1, 1, %70;\n}\n"
        : F64(d)
        : "r"(a0), "r"(a1), "r"(a2), "r"(a3), "l"(desc), "r"(scale_d), "n"(TB));
}
__device__ __forceinline__ void fence_regs(float (&d)[64]) {
#pragma unroll
    for (int i = 0; i < 64; i++) asm volatile("" : "+f"(d[i])::"memory");
}
__device__ __forceinline__ void fence_regs(uint32_t (&d)[32]) {
#pragma unroll
    for (int i = 0; i < 32; i++) asm volatile("" : "+r"(d[i])::"memory");
}

struct DqItem { int kv, head, p, tok; };
__device__ __forceinline__ DqItem item_decode(int it, int h0, int h0inv) {
    DqItem d;
    const int su = it / ITEMS_PER_UNIT, part = it % ITEMS_PER_UNIT;
    if (su < UNITS_PER_HEAD * h0) { d.p = (su * h0inv) >> 16; d.head = su - d.p * h0; }
    else { const int x = su - UNITS_PER_HEAD * h0; d.head = h0 + x / UNITS_PER_HEAD; d.p = x % UNITS_PER_HEAD; }
    int blk;
    if (d.p == 0) { d.kv = 0; blk = 0; }
    else if (d.p == UNITS_PER_HEAD - 1) { d.kv = 1; blk = NBLK - 1; }
    else if (d.p & 1) { d.kv = 0; blk = (d.p + 1) >> 1; }
    else { d.kv = 1; blk = (d.p >> 1) - 1; }
    d.tok = blk * BN + part * 4;
    return d;
}
struct DqPtrs {
    const int* qk; const int* qv;
    const __nv_bfloat16 *ks, *kz, *vs, *vz;
};
__device__ __forceinline__ uint8_t* kv_tile(int kv, int head, int blk) {
    return reinterpret_cast<uint8_t*>(g_kv) + (size_t)((kv * HKV + head) * NBLK + blk) * TILE_BYTES;
}
__device__ __forceinline__ uint32_t codes_bf2(int a, int b) { return pack_bf16(__int2float_rn(a), __int2float_rn(b)); }
__device__ __forceinline__ void k_scale_split(uint32_t s, uint32_t& hi, uint32_t& lo) {
    const float f0 = __uint_as_float(s << 16) * SCALE_LOG2, f1 = __uint_as_float(s & 0xffff0000u) * SCALE_LOG2;
    hi = pack_bf16(f0, f1);
    lo = pack_bf16(f0 - __uint_as_float(hi << 16), f1 - __uint_as_float(hi & 0xffff0000u));
}
__device__ __forceinline__ uint32_t dq_k(int a, int b, uint32_t z, uint32_t hi, uint32_t lo) {
    const uint32_t t = bf2_sub(codes_bf2(a, b), z);
    return bf2_fma(t, hi, bf2_mul(t, lo));
}
__device__ __forceinline__ uint32_t dq_v(int a, int b, uint32_t z, uint32_t s) { return bf2_mul(bf2_sub(codes_bf2(a, b), z), s); }

__device__ __forceinline__ void ldg_stream2(int& a, int& b, const int* p, uint64_t pol) {
    asm volatile("ld.global.nc.L1::no_allocate.L2::cache_hint.v2.s32 {%0, %1}, [%2], %3;" : "=r"(a), "=r"(b) : "l"(p), "l"(pol));
}
__device__ __forceinline__ void ldg_stream4(int& a, int& b, int& c, int& d, const int* p, uint64_t pol) {
    asm volatile("ld.global.nc.L1::no_allocate.L2::cache_hint.v4.s32 {%0, %1, %2, %3}, [%4], %5;" : "=r"(a), "=r"(b), "=r"(c), "=r"(d) : "l"(p), "l"(pol));
}
__device__ __forceinline__ void dq_load(int (&v)[16], uint32_t (&zs)[4], const DqItem& d, int lane, const DqPtrs& g, uint64_t pol) {
    if (d.kv == 0) {
        const int* src = g.qk + (size_t)(d.head * SEQ + d.tok) * DH + 4 * lane;
#pragma unroll
        for (int r = 0; r < 4; r++) ldg_stream4(v[4 * r], v[4 * r + 1], v[4 * r + 2], v[4 * r + 3], src + r * DH, pol);
        const int so = (d.head * NGK + d.tok / GRP) * DH + 4 * lane;
        const uint2 zz = __ldg(reinterpret_cast<const uint2*>(g.kz + so)), ss = __ldg(reinterpret_cast<const uint2*>(g.ks + so));
        zs[0] = zz.x; zs[1] = zz.y; zs[2] = ss.x; zs[3] = ss.y;
    } else {
        const int tk = d.head * SEQ + d.tok + (lane >> 4);
        const int* src = g.qv + (size_t)tk * DH + 32 * ((lane & 15) >> 2) + 2 * (lane & 3);
        const unsigned short* z = reinterpret_cast<const unsigned short*>(g.vz) + tk;
        const unsigned short* sc = reinterpret_cast<const unsigned short*>(g.vs) + tk;
#pragma unroll
        for (int r = 0; r < 2; r++) {
#pragma unroll
            for (int c = 0; c < 4; c++) ldg_stream2(v[8 * r + 2 * c], v[8 * r + 2 * c + 1], src + 2 * r * DH + 8 * c, pol);
            zs[r] = __ldg(z + 2 * r); zs[2 + r] = __ldg(sc + 2 * r);
        }
    }
}
__device__ __forceinline__ void dq_convert_store(const int (&v)[16], const uint32_t (&zs)[4], const DqItem& d, int lane) {
    const int tr = d.tok % BN;
    uint8_t* tile = kv_tile(d.kv, d.head, d.tok / BN);
    if (d.kv == 0) {
        uint32_t h0, l0, h1, l1;
        k_scale_split(zs[2], h0, l0); k_scale_split(zs[3], h1, l1);
        uint8_t* dst = tile + (lane >> 4) * (TILE_BYTES / 2) + (lane & 1) * 8 + tr * 128;
        const int ch = (lane & 15) >> 1;
#pragma unroll
        for (int r = 0; r < 4; r++)
            *reinterpret_cast<uint2*>(dst + r * 128 + ((ch ^ ((tr + r) & 7)) << 4)) =
                make_uint2(dq_k(v[4 * r], v[4 * r + 1], zs[0], h0, l0), dq_k(v[4 * r + 2], v[4 * r + 3], zs[1], h1, l1));
    } else {
        const int i = (lane & 15) >> 2, ch = 4 * (i & 1) + (lane & 3), t0 = tr + (lane >> 4);
        uint8_t* dst = tile + (i >> 1) * (TILE_BYTES / 2) + t0 * 128;
#pragma unroll
        for (int r = 0; r < 2; r++) {
            const uint32_t z = zs[r] * 0x10001u, s = zs[2 + r] * 0x10001u;
            *reinterpret_cast<uint4*>(dst + 2 * r * 128 + ((ch ^ ((t0 + 2 * r) & 7)) << 4)) =
                make_uint4(dq_v(v[8 * r], v[8 * r + 1], z, s), dq_v(v[8 * r + 2], v[8 * r + 3], z, s),
                           dq_v(v[8 * r + 4], v[8 * r + 5], z, s), dq_v(v[8 * r + 6], v[8 * r + 7], z, s));
        }
    }
}
__device__ __forceinline__ void dq_signal(const DqItem& d, int lane) {
    asm volatile("fence.proxy.async.global;" ::: "memory");
    __syncwarp();
    if (lane == 0) asm volatile("red.release.gpu.global.add.u32 [%0], 1;" ::"l"(g_cnt + d.head * UNITS_PER_HEAD + d.p) : "memory");
}
__device__ __forceinline__ void dequant_loop(int it, int stride, int end, int h0, int h0inv, int lane, const DqPtrs& g, uint64_t pol) {
    if (it >= end) return;
    DqItem d = item_decode(it, h0, h0inv);
    int v[16]; uint32_t zs[4];
    dq_load(v, zs, d, lane, g, pol);
    while (true) {
        dq_convert_store(v, zs, d, lane);
        const DqItem dc = d;
        it += stride;
        const bool more = it < end;
        if (more) {
            d = item_decode(it, h0, h0inv);
            dq_load(v, zs, d, lane, g, pol);
        }
        dq_signal(dc, lane);
        if (!more) break;
    }
}
__device__ __forceinline__ void dq_bulk_zs(uint32_t (&zs)[16], const DqItem& d, int lane, const DqPtrs& g) {
    if (d.kv == 0) {
        const int so = (d.head * NGK + d.tok / GRP) * DH + 4 * lane;
        const uint2 zz = __ldg(reinterpret_cast<const uint2*>(g.kz + so)), ss = __ldg(reinterpret_cast<const uint2*>(g.ks + so));
        zs[0] = zz.x; zs[1] = zz.y; zs[2] = ss.x; zs[3] = ss.y;
    } else {
        const uint4* z = reinterpret_cast<const uint4*>(g.vz + d.head * SEQ + d.tok);
        const uint4* s = reinterpret_cast<const uint4*>(g.vs + d.head * SEQ + d.tok);
        const uint4 z0 = __ldg(z), z1 = __ldg(z + 1), s0 = __ldg(s), s1 = __ldg(s + 1);
        zs[0] = z0.x; zs[1] = z0.y; zs[2] = z0.z; zs[3] = z0.w; zs[4] = z1.x; zs[5] = z1.y; zs[6] = z1.z; zs[7] = z1.w;
        zs[8] = s0.x; zs[9] = s0.y; zs[10] = s0.z; zs[11] = s0.w; zs[12] = s1.x; zs[13] = s1.y; zs[14] = s1.z; zs[15] = s1.w;
    }
}
__device__ __forceinline__ void dq_bulk_convert(const int (&v)[64], const uint32_t (&zs)[16], int kv, uint32_t dst, int lane) {
    if (kv == 0) {
        uint32_t h0, l0, h1, l1;
        k_scale_split(zs[2], h0, l0); k_scale_split(zs[3], h1, l1);
        const uint32_t a = dst + (lane >> 4) * 2048 + (lane & 1) * 8;
        const int ch = (lane & 15) >> 1;
#pragma unroll
        for (int r = 0; r < 16; r++)
            asm volatile("st.shared.v2.u32 [%0], {%1, %2};" ::"r"(a + r * 128 + ((ch ^ (r & 7)) << 4)),
                         "r"(dq_k(v[4 * r], v[4 * r + 1], zs[0], h0, l0)), "r"(dq_k(v[4 * r + 2], v[4 * r + 3], zs[1], h1, l1)) : "memory");
    } else {
        const int i = lane >> 3, c = (lane & 7) >> 1, ch = 4 * (i & 1) + 2 * (lane & 1);
        const uint32_t a = dst + (i >> 1) * 2048 + 4 * c;
#pragma unroll
        for (int r = 0; r < 16; r++) {
            const uint32_t sel = (r & 1) ? 0x3232u : 0x1010u;
            const uint32_t z = __byte_perm(zs[r >> 1], 0, sel), s = __byte_perm(zs[8 + (r >> 1)], 0, sel);
            asm volatile("st.shared.u32 [%0], %1;" ::"r"(a + r * 128 + ((ch ^ (r & 7)) << 4)), "r"(dq_v(v[4 * r], v[4 * r + 1], z, s)) : "memory");
            asm volatile("st.shared.u32 [%0], %1;" ::"r"(a + r * 128 + (((ch + 1) ^ (r & 7)) << 4)), "r"(dq_v(v[4 * r + 2], v[4 * r + 3], z, s)) : "memory");
        }
    }
}

template <int V> struct IC { static constexpr int value = V; };
struct Ring {
    uint32_t slot, phase;
    __device__ __forceinline__ void advance() { if (++slot == NS) { slot = 0; phase ^= 1; } }
};

__device__ __forceinline__ void load_q(uint32_t (&qf)[32], uint32_t qrow, uint32_t qsw) {
#pragma unroll
    for (int kk = 0; kk < 8; kk++)
        asm volatile("ldmatrix.sync.aligned.m8n8.x4.shared.b16 {%0, %1, %2, %3}, [%4];"
                     : "=r"(qf[4 * kk]), "=r"(qf[4 * kk + 1]), "=r"(qf[4 * kk + 2]), "=r"(qf[4 * kk + 3])
                     : "r"(qrow + (kk >> 2) * (QBUF_BYTES / 2) + (qsw ^ ((kk & 3) << 5))) : "memory");
}
__device__ __forceinline__ void issue_qk(float (&S)[64], const uint32_t (&qf)[32], uint32_t kaddr) {
    const uint64_t hi = (uint64_t)(64u | (1u << 30)) << 32;
    const uint32_t lo = ((kaddr & 0x3FFFFu) >> 4) | (1u << 16);
#pragma unroll
    for (int kk = 0; kk < 8; kk++)
        wgmma_rs<0>(S, qf[4 * kk], qf[4 * kk + 1], qf[4 * kk + 2], qf[4 * kk + 3],
                    hi | (uint64_t)(lo + (kk >> 2) * 1024 + (kk & 3) * 2), kk != 0);
}
__device__ __forceinline__ void issue_pv(float (&O)[64], const uint32_t (&P)[32], uint32_t vaddr, int acc) {
    const uint64_t hi = (uint64_t)(64u | (1u << 30)) << 32;
    const uint32_t lo = ((vaddr & 0x3FFFFu) >> 4) | (1024u << 16);
#pragma unroll
    for (int kk = 0; kk < 8; kk++)
        wgmma_rs<1>(O, P[4 * kk], P[4 * kk + 1], P[4 * kk + 2], P[4 * kk + 3], hi | (uint64_t)(lo + kk * 128), kk != 0 ? 1 : acc);
}
template <int J0, int J1>
__device__ __forceinline__ void exp_part(float (&S)[64], float (&acc)[4]) {
#pragma unroll
    for (int j = J0; j < J1; j++) {
        S[4 * j + 0] = ex2(S[4 * j + 0]);
        S[4 * j + 1] = ex2(S[4 * j + 1]);
        S[4 * j + 2] = ex2(S[4 * j + 2]);
        S[4 * j + 3] = ex2(S[4 * j + 3]);
        if (j == 0) { acc[0] = S[0]; acc[1] = S[1]; acc[2] = S[2]; acc[3] = S[3]; }
        else { acc[0] += S[4 * j + 0]; acc[1] += S[4 * j + 1]; acc[2] += S[4 * j + 2]; acc[3] += S[4 * j + 3]; }
    }
}
__device__ __forceinline__ void cvt_p(const float (&S)[64], uint32_t (&P)[32]) {
#pragma unroll
    for (int j = 0; j < 16; j++) {
        P[2 * j] = pack_bf16(S[4 * j], S[4 * j + 1]);
        P[2 * j + 1] = pack_bf16(S[4 * j + 2], S[4 * j + 3]);
    }
}
__device__ __forceinline__ bool store_o(const float (&O)[64], float l0, float l1, __nv_bfloat16* __restrict__ orow) {
    l0 += __shfl_xor_sync(0xffffffffu, l0, 1); l1 += __shfl_xor_sync(0xffffffffu, l1, 1);
    l0 += __shfl_xor_sync(0xffffffffu, l0, 2); l1 += __shfl_xor_sync(0xffffffffu, l1, 2);
    const float i0 = __fdividef(1.0f, l0), i1 = __fdividef(1.0f, l1);
    float c0 = 0.f, c1 = 0.f, c2 = 0.f, c3 = 0.f;
#pragma unroll
    for (int i = 0; i < 4; i++) {
        uint4 a, b;
        a.x = pack_bf16(O[16 * i + 0] * i0, O[16 * i + 1] * i0);
        a.y = pack_bf16(O[16 * i + 4] * i0, O[16 * i + 5] * i0);
        a.z = pack_bf16(O[16 * i + 8] * i0, O[16 * i + 9] * i0);
        a.w = pack_bf16(O[16 * i + 12] * i0, O[16 * i + 13] * i0);
        b.x = pack_bf16(O[16 * i + 2] * i1, O[16 * i + 3] * i1);
        b.y = pack_bf16(O[16 * i + 6] * i1, O[16 * i + 7] * i1);
        b.z = pack_bf16(O[16 * i + 10] * i1, O[16 * i + 11] * i1);
        b.w = pack_bf16(O[16 * i + 14] * i1, O[16 * i + 15] * i1);
        *reinterpret_cast<uint4*>(orow + 32 * i) = a;
        *reinterpret_cast<uint4*>(orow + 8 * DH + 32 * i) = b;
#pragma unroll
        for (int e = 0; e < 16; e += 4) {
            c0 = fmaf(O[16 * i + e], 0.f, c0); c1 = fmaf(O[16 * i + e + 1], 0.f, c1);
            c2 = fmaf(O[16 * i + e + 2], 0.f, c2); c3 = fmaf(O[16 * i + e + 3], 0.f, c3);
        }
    }
    return l0 >= L_MIN && l0 <= L_MAX && l1 >= L_MIN && l1 <= L_MAX && (c0 + c1) + (c2 + c3) == 0.f;
}

__global__ void __cluster_dims__(2, 1, 1) __launch_bounds__(384, 1)
attn_kernel(const __grid_constant__ CUtensorMap qmap, const int* __restrict__ qk, const int* __restrict__ qv,
            const __nv_bfloat16* __restrict__ ks, const __nv_bfloat16* __restrict__ kz,
            const __nv_bfloat16* __restrict__ vs, const __nv_bfloat16* __restrict__ vz,
            __nv_bfloat16* __restrict__ out) {
    extern __shared__ __align__(1024) uint8_t smem_raw[];
    const uint32_t sb = smem_u32(smem_raw);
    const uint32_t qbuf = sb + NS * TILE_BYTES;
    const uint32_t bar_full = qbuf + QBUF_BYTES, bar_empty = bar_full + 8 * NS;
    const uint32_t bar_qfull = bar_empty + 8 * NS, bar_qempty = bar_qfull + 8, pin_addr = bar_qempty + 8;
    const uint32_t bar_bempty = pin_addr + 8;
    const uint32_t bar_rfull = bar_bempty + 8 * NIN, bar_rempty = bar_rfull + 16;
    const uint32_t bar_bfull = bar_rempty + 16, bar_bdone = bar_bfull + 8 * MAX_CHUNKS_PER_CTA;
    volatile uint8_t* redo = smem_raw + NS * TILE_BYTES + QBUF_BYTES + 1024;
    const int wg = __shfl_sync(0xffffffffu, threadIdx.x >> 7, 0);
    const int warp = __shfl_sync(0xffffffffu, (threadIdx.x >> 5) & 3, 0);
    const int lane = threadIdx.x & 31;
    uint32_t rank; asm("mov.u32 %0, %%cluster_ctarank;" : "=r"(rank));
    const int cluster_id = blockIdx.x >> 1, nclusters = gridDim.x >> 1;

    DBG_STAMP(0);
    const int rem = NTILES % nclusters;
    const int nlight = rem ? nclusters - rem : 0;
    const bool bulk = nlight >= MIN_LIGHT;
    const bool light = bulk && cluster_id >= rem;
    const int h0 = min(HKV, ((bulk ? rem : nclusters) + TILES_PER_HEAD - 1) / TILES_PER_HEAD);
    const int h0inv = (65536 + h0 - 1) / h0;
    const int nhelp = (bulk ? 2 * rem : (int)gridDim.x) * 3;
    const int nfirst = bulk ? min(NITEMS, (nhelp * NFIRST) & ~(ITEMS_PER_CHUNK - 1)) : NITEMS;
    const int chunk0 = nfirst / ITEMS_PER_CHUNK + (int)blockIdx.x - 2 * rem, chunk_stride = 2 * nlight;
    const int nchunks = light ? (NCHUNKS - chunk0 + chunk_stride - 1) / chunk_stride : 0;
    const DqPtrs dq{qk, qv, ks, kz, vs, vz};
    uint64_t pol;
    asm volatile("createpolicy.fractional.L2::evict_first.b64 %0, 1.0;" : "=l"(pol));
    const int gwarp = wg * 4 + warp;

    if (gwarp == 0) {
        if (lane == 0) {
            if (sb & 1023u) __trap();
            for (int s = 0; s < NS; s++) { mbar_init(bar_full + 8 * s, 1); mbar_init(bar_empty + 8 * s, 4); }
            mbar_init(bar_qfull, 1); mbar_init(bar_qempty, 8);
            for (int s = 0; s < 2; s++) { mbar_init(bar_rfull + 8 * s, 1); mbar_init(bar_rempty + 8 * s, 2); }
            if (light) {
                for (int s = 0; s < NIN; s++) mbar_init(bar_bempty + 8 * s, 4);
                for (int s = 0; s < nchunks; s++) { mbar_init(bar_bfull + 8 * s, 1); mbar_init(bar_bdone + 8 * s, 4); }
            }
            asm volatile("fence.mbarrier_init.release.cluster;\nfence.acq_rel.cta;" ::: "memory");
            mbar_expect_tx(bar_qfull, QBUF_BYTES);
            tma_load_2d(qbuf, &qmap, 0, cluster_id * 256 + rank * 128, bar_qfull);
            tma_load_2d(qbuf + QBUF_BYTES / 2, &qmap, 64, cluster_id * 256 + rank * 128, bar_qfull);
        }
        __syncwarp();
        cluster_arrive();
        if (light) {
            if (lane == 0) {
                auto chunk_src = [&](int k) {
                    const DqItem d = item_decode((chunk0 + k * chunk_stride) * ITEMS_PER_CHUNK, h0, h0inv);
                    return (d.kv ? qv : qk) + (size_t)(d.head * SEQ + d.tok) * DH;
                };
                for (int k = 0; k < nchunks; k++) {
                    const int slot = k % NIN;
                    if (PFD > 0) {
                        if (k == 0) { for (int i = NIN; i < NIN + PFD - 1 && i < nchunks; i++) asm volatile("cp.async.bulk.prefetch.L2.global [%0], %1;" ::"l"(chunk_src(i)), "r"(TILE_BYTES) : "memory"); }
                        if (k + NIN + PFD - 1 < nchunks) asm volatile("cp.async.bulk.prefetch.L2.global [%0], %1;" ::"l"(chunk_src(k + NIN + PFD - 1)), "r"(TILE_BYTES) : "memory");
                    }
                    mbar_wait(bar_bempty + 8 * slot, ((k / NIN) & 1) ^ 1);
                    mbar_expect_tx(bar_bfull + 8 * k, TILE_BYTES);
                    bulk_load_hint(sb + slot * TILE_BYTES, chunk_src(k), TILE_BYTES, bar_bfull + 8 * k, pol);
                }
            }
            __syncwarp();
        }
        cluster_wait();
    } else {
        cluster_arrive();
        if (light || wg != 0) cluster_wait();
        if (light && gwarp == 1) {
            if (lane == 0) {
                for (int sig = 0; sig < nchunks;) {
                    mbar_wait(bar_bdone + 8 * sig, 0);
                    int m = 1;
                    while (m < 4 && sig + m < nchunks && mbar_test(bar_bdone + 8 * (sig + m), 0)) m++;
                    asm volatile("fence.acq_rel.gpu;" ::: "memory");
                    for (int i = 0; i < m; i++) {
                        const DqItem d = item_decode((chunk0 + (sig + i) * chunk_stride) * ITEMS_PER_CHUNK, h0, h0inv);
                        asm volatile("red.relaxed.gpu.global.add.u32 [%0], %1;" ::"l"(g_cnt + d.head * UNITS_PER_HEAD + d.p), "r"(ITEMS_PER_CHUNK) : "memory");
                    }
                    sig += m;
                }
            }
            __syncwarp();
        } else if (light) {
            const uint32_t obuf = sb + NIN * TILE_BYTES + (gwarp - 2) * 4096;
            int j = gwarp - 2, kprev = -1;
            DqItem d;
            uint32_t zs[16];
            if (j < 4 * nchunks) { d = item_decode((chunk0 + (j >> 2) * chunk_stride) * ITEMS_PER_CHUNK + (j & 3) * 4, h0, h0inv); dq_bulk_zs(zs, d, lane, dq); }
            while (j < 4 * nchunks) {
                const int k = j >> 2, slot = k % NIN;
                mbar_wait(bar_bfull + 8 * k, 0);
                int v[64];
                const uint32_t src = sb + slot * TILE_BYTES + (j & 3) * 8192 + lane * 16;
#pragma unroll
                for (int r = 0; r < 16; r++)
                    asm volatile("ld.shared.v4.s32 {%0, %1, %2, %3}, [%4];" : "=r"(v[4 * r]), "=r"(v[4 * r + 1]), "=r"(v[4 * r + 2]), "=r"(v[4 * r + 3])
                                 : "r"(src + r * 512) : "memory");
                __syncwarp();
                if (lane == 0) {
                    mbar_arrive(bar_bempty + 8 * slot);
                    if (kprev >= 0) {
                        asm volatile("cp.async.bulk.wait_group 0;" ::: "memory");
                        mbar_arrive(bar_bdone + 8 * kprev);
                    }
                }
                __syncwarp();
                dq_bulk_convert(v, zs, d.kv, obuf, lane);
                asm volatile("fence.proxy.async.shared::cta;" ::: "memory");
                __syncwarp();
                if (lane == 0) {
                    uint8_t* o = kv_tile(d.kv, d.head, d.tok / BN) + (d.tok % BN) * 128;
                    bulk_store(o, obuf, 2048);
                    bulk_store(o + TILE_BYTES / 2, obuf + 2048, 2048);
                    asm volatile("cp.async.bulk.commit_group;" ::: "memory");
                }
                kprev = k;
                j += 10;
                if (j < 4 * nchunks) { d = item_decode((chunk0 + (j >> 2) * chunk_stride) * ITEMS_PER_CHUNK + (j & 3) * 4, h0, h0inv); dq_bulk_zs(zs, d, lane, dq); }
            }
            if (kprev >= 0 && lane == 0) {
                asm volatile("cp.async.bulk.wait_group 0;" ::: "memory");
                mbar_arrive(bar_bdone + 8 * kprev);
            }
            __syncwarp();
        }
    }
    if (light) { cluster_arrive_release(); cluster_wait(); }

    if (wg == 0) {
        asm volatile("setmaxnreg.dec.sync.aligned.u32 56;");
        if (warp == 0) {
            uint32_t qphase = 0;
            auto load_qtile = [&](int t) {
                if (lane == 0) {
                    mbar_wait(bar_qempty, qphase);
                    mbar_expect_tx(bar_qfull, QBUF_BYTES);
                    tma_load_2d(qbuf, &qmap, 0, t * 256 + rank * 128, bar_qfull);
                    tma_load_2d(qbuf + QBUF_BYTES / 2, &qmap, 64, t * 256 + rank * 128, bar_qfull);
                }
                __syncwarp();
                qphase ^= 1;
            };
            Ring r{0, 1};
            int vhead = -1;
            uint32_t vmask = 0;
            auto load = [&](int kv, int head, int blk) {
                const int p = kv == 0 ? (blk == 0 ? 0 : 2 * blk - 1) : (blk == NBLK - 1 ? UNITS_PER_HEAD - 1 : 2 * blk + 2);
                if (head != vhead) { vhead = head; vmask = 0; }
                if (!((vmask >> p) & 1)) {
                    uint32_t n = 0;
                    while (true) {
                        unsigned int c;
                        asm volatile("ld.acquire.gpu.global.u32 %0, [%1];" : "=r"(c) : "l"(g_cnt + head * UNITS_PER_HEAD + lane) : "memory");
                        vmask = __ballot_sync(0xffffffffu, c == ITEMS_PER_UNIT);
                        if ((vmask >> p) & 1) break;
                        if (++n > (1u << 22)) __trap();
                    }
                    asm volatile("fence.proxy.async.global;" ::: "memory");
                }
                if (lane == 0) {
                    mbar_wait(bar_empty + 8 * r.slot, r.phase);
                    mbar_expect_tx(bar_full + 8 * r.slot, TILE_BYTES);
                    bulk_load_mc(sb + r.slot * TILE_BYTES + rank * (TILE_BYTES / 2), kv_tile(kv, head, blk) + rank * (TILE_BYTES / 2),
                                 TILE_BYTES / 2, bar_full + 8 * r.slot, (uint16_t)3);
                }
                __syncwarp();
                r.advance();
            };
            load(0, cluster_id / TILES_PER_HEAD, 0);
            for (int t = cluster_id; t < NTILES; t += nclusters) {
                const int head = t / TILES_PER_HEAD;
                const int tn = t + nclusters;
                for (int j = 0; j < NBLK; j++) {
                    if (j == 4 && tn < NTILES) load_qtile(tn);
                    if (j < NBLK - 1) load(0, head, j + 1);
                    else if (tn < NTILES) load(0, tn / TILES_PER_HEAD, 0);
                    load(1, head, j);
                }
            }
            if (lane == 0) {
                const unsigned int prev = atomicAdd(&g_done, 1u);
                if (prev == gridDim.x - 1) {
                    for (int i = 0; i < HKV * UNITS_PER_HEAD; i++) g_cnt[i] = 0;
                    g_done = 0;
                }
            }
            __syncwarp();
            bar_sync(3, 288);
            uint32_t n = 0;
            for (int t = cluster_id, k = 0; t < NTILES; t += nclusters, k++) {
                if (!redo[k]) continue;
                load_qtile(t);
                if (lane == 0) {
                    for (int j = 0; j < 2 * NBLK; j++, n++) {
                        const uint32_t s = n & 1;
                        mbar_wait(bar_rempty + 8 * s, ((n >> 1) & 1) ^ 1);
                        mbar_expect_tx(bar_rfull + 8 * s, TILE_BYTES);
                        bulk_load(sb + s * TILE_BYTES, kv_tile(j & 1, t / TILES_PER_HEAD, j >> 1), TILE_BYTES, bar_rfull + 8 * s);
                    }
                }
                __syncwarp();
            }
        } else {
            if (!light) {
                dequant_loop(blockIdx.x * 3 + (warp - 1), nhelp, nfirst, h0, h0inv, lane, dq, pol);
                cluster_wait();
            }
        }
        cluster_arrive(); cluster_wait();
    } else {
        asm volatile("setmaxnreg.inc.sync.aligned.u32 224;");
        const int w = wg - 1;
        const int my_bar = 1 + w, other_bar = 2 - w;
        const int row_in_tile = rank * 128 + w * 64 + warp * 16 + (lane >> 2);
        const int coff = (lane & 3) * 8;
        const uint32_t qrow = qbuf + (w * 64 + warp * 16 + (lane & 15)) * 128;
        const uint32_t qsw = ((lane >> 4) ^ (lane & 7)) << 4;
        const uint32_t rem_empty = mapa(bar_empty, warp & 1);
        const bool releaser = lane == 0 && warp < 2;
        uint32_t qf[32], P[32];
        float S[64], O[64];
        float l0 = 0.f, l1 = 0.f, lo0 = 1.f, lo1 = 1.f;
        uint32_t qphase = 0;
        Ring r{0, 0};
        auto release = [&]() {
            if (releaser) mbar_arrive_remote(rem_empty + 8 * r.slot);
            r.advance();
        };
        auto reload_q = [&]() {
            mbar_wait(bar_qfull, qphase);
            qphase ^= 1;
            load_q(qf, qrow, qsw);
            __syncwarp();
            if (lane == 0) mbar_arrive(bar_qempty);
        };
        auto pin = [&](float x) {
            asm volatile("{\n.reg .pred p;\nsetp.eq.f32 p, %0, 0fBF800000;\n@p st.shared.f32 [%1], %0;\n}\n" ::"f"(x), "r"(pin_addr) : "memory");
        };
        int t = cluster_id, tk = 0;
#pragma unroll
        for (int i = 0; i < 64; i++) { S[i] = 0.f; O[i] = 0.f; }
        if (gwarp == 4) { reinterpret_cast<volatile uint32_t*>(redo)[lane] = 0; reinterpret_cast<volatile uint32_t*>(redo)[lane + 32] = 0; }
        DBG_IT(0);
        if (w == 1) bar_arrive(1, 256);
        reload_q();
        {
            mbar_wait(bar_full + 8 * r.slot, r.phase);
            bar_sync(my_bar, 256);
            wg_fence();
            issue_qk(S, qf, sb + r.slot * TILE_BYTES);
            wg_commit();
            bar_arrive(other_bar, 256);
            wg_wait<0>();
            fence_regs(S);
            release();
            float acc[4];
            exp_part<0, 16>(S, acc);
            l0 = acc[0] + acc[1]; l1 = acc[2] + acc[3];
            cvt_p(S, P);
        }
        uint32_t ready = 0;
        auto step = [&](auto first, bool store_prev, __nv_bfloat16* orow, bool swap_l, bool new_q) {
            constexpr bool FIRST = decltype(first)::value;
            const uint32_t kslot = r.slot;
            Ring rv = r; rv.advance();
            if (!ready) {
                mbar_wait(bar_full + 8 * r.slot, r.phase);
                mbar_wait(bar_full + 8 * rv.slot, rv.phase);
            }
            bar_sync(my_bar, 256);
            wg_fence();
            issue_qk(S, qf, sb + kslot * TILE_BYTES);
            wg_commit();
            if (FIRST) {
                if (store_prev) { if (!store_o(O, lo0, lo1, orow)) redo[tk - 1] = 1; }
                fence_regs(O);
                wg_fence();
            }
            issue_pv(O, P, sb + rv.slot * TILE_BYTES, !FIRST);
            wg_commit();
            bar_arrive(other_bar, 256);
            wg_wait<1>();
            fence_regs(S);
            release();
            if (!FIRST && new_q) { fence_regs(qf); reload_q(); }
            float acc[4];
            exp_part<0, PIN_J>(S, acc);
            pin((acc[0] + acc[1]) + (acc[2] + acc[3]));
            wg_wait<0>();
            fence_regs(O);
            fence_regs(P);
            release();
            {
                Ring rn = r; rn.advance();
                ready = mbar_test(bar_full + 8 * r.slot, r.phase) & mbar_test(bar_full + 8 * rn.slot, rn.phase);
            }
            exp_part<PIN_J, 16>(S, acc);
            cvt_p(S, P);
            if (!FIRST && swap_l) { lo0 = l0; lo1 = l1; l0 = 0.f; l1 = 0.f; }
            l0 += acc[0] + acc[1]; l1 += acc[2] + acc[3];
        };
        DBG_STAMP(1);
        __nv_bfloat16* oprev = out;
        while (true) {
            const int tn = t + nclusters;
            const bool has_next = tn < NTILES;
            step(IC<1>{}, tk > 0, oprev, false, false);
            const int jend = has_next ? NBLK : NBLK - 1;
#pragma unroll 1
            for (int j = 1; j < jend; j++) step(IC<0>{}, false, nullptr, j == NBLK - 1, has_next && j == NBLK - 2);
            oprev = out + (size_t)(t * 256 + row_in_tile) * DH + coff;
            if (has_next) {
                t = tn; tk++;
            } else {
                mbar_wait(bar_full + 8 * r.slot, r.phase);
                bar_sync(my_bar, 256);
                wg_fence();
                issue_pv(O, P, sb + r.slot * TILE_BYTES, 1);
                wg_commit();
                if (w == 0) bar_arrive(other_bar, 256);
                wg_wait<0>();
                fence_regs(O);
                release();
                if (!store_o(O, l0, l1, oprev)) redo[tk] = 1;
                break;
            }
        }
        bar_sync(3, 288);
        uint32_t n = 0;
        for (int tt = cluster_id, k = 0; tt < NTILES; tt += nclusters, k++) {
            if (!redo[k]) continue;
            mbar_wait(bar_qfull, qphase);
            qphase ^= 1;
            float m0 = -INFINITY, m1 = -INFINITY;
            l0 = 0.f; l1 = 0.f;
#pragma unroll 1
            for (int j = 0; j < NBLK; j++) {
                load_q(qf, qrow, qsw);
                mbar_wait(bar_rfull + 8 * (n & 1), (n >> 1) & 1);
                wg_fence();
                issue_qk(S, qf, sb + (n & 1) * TILE_BYTES);
                wg_commit();
                wg_wait<0>();
                fence_regs(S);
                if (warp == 0 && lane == 0) mbar_arrive(bar_rempty + 8 * (n & 1));
                n++;
                float a0 = m0, a1 = m1;
#pragma unroll
                for (int i = 0; i < 16; i++) {
                    a0 = fmaxf(a0, fmaxf(S[4 * i], S[4 * i + 1]));
                    a1 = fmaxf(a1, fmaxf(S[4 * i + 2], S[4 * i + 3]));
                }
                a0 = fmaxf(a0, __shfl_xor_sync(0xffffffffu, a0, 1)); a1 = fmaxf(a1, __shfl_xor_sync(0xffffffffu, a1, 1));
                a0 = fmaxf(a0, __shfl_xor_sync(0xffffffffu, a0, 2)); a1 = fmaxf(a1, __shfl_xor_sync(0xffffffffu, a1, 2));
                const float al0 = ex2(m0 - a0), al1 = ex2(m1 - a1);
                m0 = a0; m1 = a1;
#pragma unroll
                for (int i = 0; i < 16; i++) {
                    S[4 * i] -= a0; S[4 * i + 1] -= a0; S[4 * i + 2] -= a1; S[4 * i + 3] -= a1;
                    O[4 * i] *= al0; O[4 * i + 1] *= al0; O[4 * i + 2] *= al1; O[4 * i + 3] *= al1;
                }
                float acc[4];
                exp_part<0, 16>(S, acc);
                l0 = l0 * al0 + (acc[0] + acc[1]); l1 = l1 * al1 + (acc[2] + acc[3]);
                cvt_p(S, P);
                mbar_wait(bar_rfull + 8 * (n & 1), (n >> 1) & 1);
                wg_fence();
                issue_pv(O, P, sb + (n & 1) * TILE_BYTES, j != 0);
                wg_commit();
                wg_wait<0>();
                fence_regs(O);
                if (warp == 0 && lane == 0) mbar_arrive(bar_rempty + 8 * (n & 1));
                n++;
            }
            __syncwarp();
            if (lane == 0) mbar_arrive(bar_qempty);
            store_o(O, l0, l1, out + (size_t)(tt * 256 + row_in_tile) * DH + coff);
        }
        cluster_arrive(); cluster_wait();
    }
}

}

extern "C" void kernel_launch(void* const* d_in, const int* in_sizes, int n_in, void* d_out, int out_size) {
    const __nv_bfloat16* q = (const __nv_bfloat16*)d_in[0];
    const int* qk = (const int*)d_in[1];
    const int* qv = (const int*)d_in[2];
    const __nv_bfloat16* ks = (const __nv_bfloat16*)d_in[3];
    const __nv_bfloat16* kz = (const __nv_bfloat16*)d_in[4];
    const __nv_bfloat16* vs = (const __nv_bfloat16*)d_in[5];
    const __nv_bfloat16* vz = (const __nv_bfloat16*)d_in[6];
    typedef CUresult (*EncodeFn)(CUtensorMap*, CUtensorMapDataType, cuuint32_t, void*, const cuuint64_t*, const cuuint64_t*,
                                 const cuuint32_t*, const cuuint32_t*, CUtensorMapInterleave, CUtensorMapSwizzle,
                                 CUtensorMapL2promotion, CUtensorMapFloatOOBfill);
    static EncodeFn encode = nullptr;
    static int grid = 0;
    if (grid == 0) {
        void* fn = nullptr;
        cudaDriverEntryPointQueryResult qr;
        cudaGetDriverEntryPoint("cuTensorMapEncodeTiled", &fn, cudaEnableDefault, &qr);
        encode = (EncodeFn)fn;
        cudaFuncSetAttribute(attn_kernel, cudaFuncAttributeMaxDynamicSharedMemorySize, SMEM_BYTES);
        cudaLaunchConfig_t cfg = {};
        cfg.gridDim = dim3(2, 1, 1); cfg.blockDim = dim3(384, 1, 1); cfg.dynamicSmemBytes = SMEM_BYTES;
        cudaLaunchAttribute at[1];
        at[0].id = cudaLaunchAttributeClusterDimension;
        at[0].val.clusterDim.x = 2; at[0].val.clusterDim.y = 1; at[0].val.clusterDim.z = 1;
        cfg.attrs = at; cfg.numAttrs = 1;
        int nc = 0;
        if (cudaOccupancyMaxActiveClusters(&nc, attn_kernel, &cfg) != cudaSuccess || nc <= 0) { nc = 1; (void)cudaGetLastError(); }
        if (nc > NTILES) nc = NTILES;
        if (FORCE_CLUSTERS) nc = FORCE_CLUSTERS;
        grid = nc * 2;
    }
    CUtensorMap qmap;
    const cuuint64_t dims[2] = {(cuuint64_t)DH, (cuuint64_t)HQ * SEQ};
    const cuuint64_t strides[1] = {(cuuint64_t)DH * 2};
    const cuuint32_t box[2] = {64, 128};
    const cuuint32_t estr[2] = {1, 1};
    encode(&qmap, CU_TENSOR_MAP_DATA_TYPE_BFLOAT16, 2, (void*)q, dims, strides, box, estr, CU_TENSOR_MAP_INTERLEAVE_NONE,
           CU_TENSOR_MAP_SWIZZLE_128B, CU_TENSOR_MAP_L2_PROMOTION_L2_128B, CU_TENSOR_MAP_FLOAT_OOB_FILL_NONE);
    attn_kernel<<<grid, 384, SMEM_BYTES>>>(qmap, qk, qv, ks, kz, vs, vz, (__nv_bfloat16*)d_out);
}
```

```cpp
#include <cuda_runtime.h>
#include <cuda_bf16.h>
#include <cuda.h>
#include <stdint.h>

#define PIN_J 7
#define LOADER_DELAY 2000
#define NFIRST 2
#define FORCE_CLUSTERS 0

namespace {

constexpr int HQ = 32, HKV = 8, SEQ = 2048, DH = 128, NGK = 2, GRP = SEQ / NGK;
constexpr int BN = 128, NBLK = SEQ / BN;
constexpr int TILE_BYTES = BN * DH * 2;
constexpr int NS = 6;
constexpr int NST = NS / 2;
constexpr int STAGE_BYTES = 2 * TILE_BYTES;
constexpr int NTILES = HQ * SEQ / 256;
constexpr int TILES_PER_HEAD = NTILES / HKV;
constexpr int QBUF_BYTES = 128 * DH * 2;
constexpr int SMEM_BYTES = NS * TILE_BYTES + QBUF_BYTES + 2048;
constexpr int UNITS_PER_HEAD = 2 * NBLK;
constexpr int ITEMS_PER_UNIT = 32;
constexpr int NITEMS = HKV * UNITS_PER_HEAD * ITEMS_PER_UNIT;
constexpr int ITEMS_PER_CHUNK = 16;
constexpr int NCHUNKS = NITEMS / ITEMS_PER_CHUNK;
constexpr int MIN_LIGHT = 6;
constexpr int MAX_CHUNKS_PER_CTA = (NCHUNKS + 2 * MIN_LIGHT - 1) / (2 * MIN_LIGHT);
constexpr int NIN = 4;
constexpr float SCALE_LOG2 = 0.08838834764831845f * 1.4426950408889634f;
constexpr float L_MIN = 9.094947017729282e-13f, L_MAX = 1099511627776.0f;

__device__ __align__(1024) uint4 g_kv[2 * HKV * NBLK * (TILE_BYTES / 16)];
__device__ __align__(128) unsigned int g_cnt[HKV * UNITS_PER_HEAD];
__device__ unsigned int g_done;

__device__ __forceinline__ uint32_t smem_u32(const void* p) { return (uint32_t)__cvta_generic_to_shared(p); }

__device__ __forceinline__ void mbar_init(uint32_t a, uint32_t cnt) {
    asm volatile("mbarrier.init.shared::cta.b64 [%0], %1;" ::"r"(a), "r"(cnt) : "memory");
}
__device__ __forceinline__ void mbar_expect_tx(uint32_t a, uint32_t bytes) {
    asm volatile("mbarrier.arrive.expect_tx.shared::cta.b64 _, [%0], %1;" ::"r"(a), "r"(bytes) : "memory");
}
__device__ __forceinline__ void mbar_wait(uint32_t a, uint32_t parity) {
    asm volatile(
        "{\n"
        ".reg .pred p;\n"
        ".reg .u32 n;\n"
        "mbarrier.try_wait.parity.shared::cta.b64 p, [%0], %1;\n"
        "@p bra WAIT_DONE;\n"
        "mov.u32 n, 0;\n"
        "WAIT_LOOP:\n"
        "mbarrier.try_wait.parity.shared::cta.b64 p, [%0], %1;\n"
        "@p bra WAIT_DONE;\n"
        "add.u32 n, n, 1;\n"
        "setp.lt.u32 p, n, 0x1000000;\n"
        "@p bra WAIT_LOOP;\n"
        "trap;\n"
        "WAIT_DONE:\n"
        "}\n" ::"r"(a), "r"(parity) : "memory");
}
__device__ __forceinline__ uint32_t mbar_test(uint32_t a, uint32_t parity) {
    uint32_t ok;
    asm volatile("{\n.reg .pred p;\nmbarrier.test_wait.parity.shared::cta.b64 p, [%1], %2;\nselp.u32 %0, 1, 0, p;\n}\n"
                 : "=r"(ok) : "r"(a), "r"(parity) : "memory");
    return ok;
}
__device__ __forceinline__ void mbar_arrive(uint32_t a) {
    asm volatile("mbarrier.arrive.shared::cta.b64 _, [%0];" ::"r"(a) : "memory");
}
__device__ __forceinline__ uint32_t mapa(uint32_t a, uint32_t cta) {
    uint32_t r; asm("mapa.shared::cluster.u32 %0, %1, %2;" : "=r"(r) : "r"(a), "r"(cta)); return r;
}
__device__ __forceinline__ void mbar_arrive_remote(uint32_t ra) {
    asm volatile("mbarrier.arrive.shared::cluster.b64 _, [%0];" ::"r"(ra) : "memory");
}
__device__ __forceinline__ void bulk_load(uint32_t dst, const void* src, uint32_t bytes, uint32_t bar) {
    asm volatile("cp.async.bulk.shared::cluster.global.mbarrier::complete_tx::bytes [%0], [%1], %2, [%3];"
        ::"r"(dst), "l"(src), "r"(bytes), "r"(bar) : "memory");
}
__device__ __forceinline__ void bulk_load_hint(uint32_t dst, const void* src, uint32_t bytes, uint32_t bar, uint64_t pol) {
    asm volatile("cp.async.bulk.shared::cluster.global.mbarrier::complete_tx::bytes.L2::cache_hint [%0], [%1], %2, [%3], %4;"
        ::"r"(dst), "l"(src), "r"(bytes), "r"(bar), "l"(pol) : "memory");
}
__device__ __forceinline__ void bulk_load_mc(uint32_t dst, const void* src, uint32_t bytes, uint32_t bar, uint16_t mask) {
    asm volatile("cp.async.bulk.shared::cluster.global.mbarrier::complete_tx::bytes.multicast::cluster [%0], [%1], %2, [%3], %4;"
        ::"r"(dst), "l"(src), "r"(bytes), "r"(bar), "h"(mask) : "memory");
}
__device__ __forceinline__ void bulk_store(void* dst, uint32_t src, uint32_t bytes) {
    asm volatile("cp.async.bulk.global.shared::cta.bulk_group [%0], [%1], %2;" ::"l"(dst), "r"(src), "r"(bytes) : "memory");
}
__device__ __forceinline__ void tma_load_2d(uint32_t dst, const CUtensorMap* map, int c0, int c1, uint32_t bar) {
    asm volatile("cp.async.bulk.tensor.2d.shared::cluster.global.mbarrier::complete_tx::bytes [%0], [%1, {%3, %4}], [%2];"
        ::"r"(dst), "l"(map), "r"(bar), "r"(c0), "r"(c1) : "memory");
}
__device__ __forceinline__ void cluster_arrive() { asm volatile("barrier.cluster.arrive.relaxed.aligned;" ::: "memory"); }
__device__ __forceinline__ void cluster_arrive_release() { asm volatile("barrier.cluster.arrive.release.aligned;" ::: "memory"); }
__device__ __forceinline__ void cluster_wait() { asm volatile("barrier.cluster.wait.aligned;" ::: "memory"); }
__device__ __forceinline__ void wg_fence() { asm volatile("wgmma.fence.sync.aligned;" ::: "memory"); }
__device__ __forceinline__ void wg_commit() { asm volatile("wgmma.commit_group.sync.aligned;" ::: "memory"); }
template <int N> __device__ __forceinline__ void wg_wait() { asm volatile("wgmma.wait_group.sync.aligned %0;" ::"n"(N) : "memory"); }
__device__ __forceinline__ void bar_sync(int id, int n) { asm volatile("bar.sync %0, %1;" ::"r"(id), "r"(n) : "memory"); }
__device__ __forceinline__ void bar_arrive(int id, int n) { asm volatile("bar.arrive %0, %1;" ::"r"(id), "r"(n) : "memory"); }

__device__ __forceinline__ float ex2(float x) { float y; asm("ex2.approx.ftz.f32 %0, %1;" : "=f"(y) : "f"(x)); return y; }
__device__ __forceinline__ uint32_t pack_bf16(float lo, float hi) {
    uint32_t r; asm("cvt.rn.bf16x2.f32 %0, %1, %2;" : "=r"(r) : "f"(hi), "f"(lo)); return r;
}
__device__ __forceinline__ uint32_t bf2_sub(uint32_t a, uint32_t b) { uint32_t r; asm("sub.rn.bf16x2 %0, %1, %2;" : "=r"(r) : "r"(a), "r"(b)); return r; }
__device__ __forceinline__ uint32_t bf2_mul(uint32_t a, uint32_t b) { uint32_t r; asm("mul.rn.bf16x2 %0, %1, %2;" : "=r"(r) : "r"(a), "r"(b)); return r; }
__device__ __forceinline__ uint32_t bf2_fma(uint32_t a, uint32_t b, uint32_t c) { uint32_t r; asm("fma.rn.bf16x2 %0, %1, %2, %3;" : "=r"(r) : "r"(a), "r"(b), "r"(c)); return r; }

#define F8(a, i) "+f"(a[i]), "+f"(a[i + 1]), "+f"(a[i + 2]), "+f"(a[i + 3]), "+f"(a[i + 4]), "+f"(a[i + 5]), "+f"(a[i + 6]), "+f"(a[i + 7])
#define F64(a) F8(a, 0), F8(a, 8), F8(a, 16), F8(a, 24), F8(a, 32), F8(a, 40), F8(a, 48), F8(a, 56)

template <int TB>
__device__ __forceinline__ void wgmma_rs(float (&d)[64], uint32_t a0, uint32_t a1, uint32_t a2, uint32_t a3, uint64_t desc, int scale_d) {
    asm volatile(
        "{\n.reg .pred p;\nsetp.ne.b32 p, %69, 0;\n"
        "wgmma.mma_async.sync.aligned.m64n128k16.f32.bf16.bf16 "
        "{%0,%1,%2,%3,%4,%5,%6,%7,%8,%9,%10,%11,%12,%13,%14,%15,"
        "%16,%17,%18,%19,%20,%21,%22,%23,%24,%25,%26,%27,%28,%29,%30,%31,"
        "%32,%33,%34,%35,%36,%37,%38,%39,%40,%41,%42,%43,%44,%45,%46,%47,"
        "%48,%49,%50,%51,%52,%53,%54,%55,%56,%57,%58,%59,%60,%61,%62,%63},"
        "{%64,%65,%66,%67}, %68, p, 1, 1, %70;\n}\n"
        : F64(d)
        : "r"(a0), "r"(a1), "r"(a2), "r"(a3), "l"(desc), "r"(scale_d), "n"(TB));
}
__device__ __forceinline__ void fence_regs(float (&d)[64]) {
#pragma unroll
    for (int i = 0; i < 64; i++) asm volatile("" : "+f"(d[i])::"memory");
}
__device__ __forceinline__ void fence_regs(uint32_t (&d)[32]) {
#pragma unroll
    for (int i = 0; i < 32; i++) asm volatile("" : "+r"(d[i])::"memory");
}

struct DqItem { int kv, head, p, tok; };
__device__ __forceinline__ DqItem item_decode(int it, int h0, int h0inv) {
    DqItem d;
    const int su = it / ITEMS_PER_UNIT, part = it % ITEMS_PER_UNIT;
    if (su < UNITS_PER_HEAD * h0) { d.p = (su * h0inv) >> 16; d.head = su - d.p * h0; }
    else { const int x = su - UNITS_PER_HEAD * h0; d.head = h0 + x / UNITS_PER_HEAD; d.p = x % UNITS_PER_HEAD; }
    int blk;
    if (d.p == 0) { d.kv = 0; blk = 0; }
    else if (d.p == UNITS_PER_HEAD - 1) { d.kv = 1; blk = NBLK - 1; }
    else if (d.p & 1) { d.kv = 0; blk = (d.p + 1) >> 1; }
    else { d.kv = 1; blk = (d.p >> 1) - 1; }
    d.tok = blk * BN + part * 4;
    return d;
}
struct DqPtrs {
    const int* qk; const int* qv;
    const __nv_bfloat16 *ks, *kz, *vs, *vz;
};
__device__ __forceinline__ uint8_t* kv_tile(int kv, int head, int blk) {
    return reinterpret_cast<uint8_t*>(g_kv) + (size_t)((kv * HKV + head) * NBLK + blk) * TILE_BYTES;
}
__device__ __forceinline__ uint32_t codes_bf2(int a, int b) { return pack_bf16(__int2float_rn(a), __int2float_rn(b)); }
__device__ __forceinline__ void k_scale_split(uint32_t s, uint32_t& hi, uint32_t& lo) {
    const float f0 = __uint_as_float(s << 16) * SCALE_LOG2, f1 = __uint_as_float(s & 0xffff0000u) * SCALE_LOG2;
    hi = pack_bf16(f0, f1);
    lo = pack_bf16(f0 - __uint_as_float(hi << 16), f1 - __uint_as_float(hi & 0xffff0000u));
}
__device__ __forceinline__ uint32_t dq_k(int a, int b, uint32_t z, uint32_t hi, uint32_t lo) {
    const uint32_t t = bf2_sub(codes_bf2(a, b), z);
    return bf2_fma(t, hi, bf2_mul(t, lo));
}
__device__ __forceinline__ uint32_t dq_v(int a, int b, uint32_t z, uint32_t s) { return bf2_mul(bf2_sub(codes_bf2(a, b), z), s); }

__device__ __forceinline__ void ldg_stream2(int& a, int& b, const int* p, uint64_t pol) {
    asm volatile("ld.global.nc.L1::no_allocate.L2::cache_hint.v2.s32 {%0, %1}, [%2], %3;" : "=r"(a), "=r"(b) : "l"(p), "l"(pol));
}
__device__ __forceinline__ void ldg_stream4(int& a, int& b, int& c, int& d, const int* p, uint64_t pol) {
    asm volatile("ld.global.nc.L1::no_allocate.L2::cache_hint.v4.s32 {%0, %1, %2, %3}, [%4], %5;" : "=r"(a), "=r"(b), "=r"(c), "=r"(d) : "l"(p), "l"(pol));
}
__device__ __forceinline__ void dq_load(int (&v)[16], uint32_t (&zs)[4], const DqItem& d, int lane, const DqPtrs& g, uint64_t pol) {
    if (d.kv == 0) {
        const int* src = g.qk + (size_t)(d.head * SEQ + d.tok) * DH + 4 * lane;
#pragma unroll
        for (int r = 0; r < 4; r++) ldg_stream4(v[4 * r], v[4 * r + 1], v[4 * r + 2], v[4 * r + 3], src + r * DH, pol);
        const int so = (d.head * NGK + d.tok / GRP) * DH + 4 * lane;
        const uint2 zz = __ldg(reinterpret_cast<const uint2*>(g.kz + so)), ss = __ldg(reinterpret_cast<const uint2*>(g.ks + so));
        zs[0] = zz.x; zs[1] = zz.y; zs[2] = ss.x; zs[3] = ss.y;
    } else {
        const int tk = d.head * SEQ + d.tok + (lane >> 4);
        const int* src = g.qv + (size_t)tk * DH + 32 * ((lane & 15) >> 2) + 2 * (lane & 3);
        const unsigned short* z = reinterpret_cast<const unsigned short*>(g.vz) + tk;
        const unsigned short* sc = reinterpret_cast<const unsigned short*>(g.vs) + tk;
#pragma unroll
        for (int r = 0; r < 2; r++) {
#pragma unroll
            for (int c = 0; c < 4; c++) ldg_stream2(v[8 * r + 2 * c], v[8 * r + 2 * c + 1], src + 2 * r * DH + 8 * c, pol);
            zs[r] = __ldg(z + 2 * r); zs[2 + r] = __ldg(sc + 2 * r);
        }
    }
}
__device__ __forceinline__ void dq_convert_store(const int (&v)[16], const uint32_t (&zs)[4], const DqItem& d, int lane) {
    const int tr = d.tok % BN;
    uint8_t* tile = kv_tile(d.kv, d.head, d.tok / BN);
    if (d.kv == 0) {
        uint32_t h0, l0, h1, l1;
        k_scale_split(zs[2], h0, l0); k_scale_split(zs[3], h1, l1);
        uint8_t* dst = tile + (lane >> 4) * (TILE_BYTES / 2) + (lane & 1) * 8 + tr * 128;
        const int ch = (lane & 15) >> 1;
#pragma unroll
        for (int r = 0; r < 4; r++)
            *reinterpret_cast<uint2*>(dst + r * 128 + ((ch ^ ((tr + r) & 7)) << 4)) =
                make_uint2(dq_k(v[4 * r], v[4 * r + 1], zs[0], h0, l0), dq_k(v[4 * r + 2], v[4 * r + 3], zs[1], h1, l1));
    } else {
        const int i = (lane & 15) >> 2, ch = 4 * (i & 1) + (lane & 3), t0 = tr + (lane >> 4);
        uint8_t* dst = tile + (i >> 1) * (TILE_BYTES / 2) + t0 * 128;
#pragma unroll
        for (int r = 0; r < 2; r++) {
            const uint32_t z = zs[r] * 0x10001u, s = zs[2 + r] * 0x10001u;
            *reinterpret_cast<uint4*>(dst + 2 * r * 128 + ((ch ^ ((t0 + 2 * r) & 7)) << 4)) =
                make_uint4(dq_v(v[8 * r], v[8 * r + 1], z, s), dq_v(v[8 * r + 2], v[8 * r + 3], z, s),
                           dq_v(v[8 * r + 4], v[8 * r + 5], z, s), dq_v(v[8 * r + 6], v[8 * r + 7], z, s));
        }
    }
}
__device__ __forceinline__ void dq_signal(const DqItem& d, int lane) {
    asm volatile("fence.proxy.async.global;" ::: "memory");
    __syncwarp();
    if (lane == 0) asm volatile("red.release.gpu.global.add.u32 [%0], 1;" ::"l"(g_cnt + d.head * UNITS_PER_HEAD + d.p) : "memory");
}
__device__ __forceinline__ void dequant_loop(int it, int stride, int end, int h0, int h0inv, int lane, const DqPtrs& g, uint64_t pol) {
    if (it >= end) return;
    DqItem d = item_decode(it, h0, h0inv);
    int v[16]; uint32_t zs[4];
    dq_load(v, zs, d, lane, g, pol);
    while (true) {
        dq_convert_store(v, zs, d, lane);
        const DqItem dc = d;
        it += stride;
        const bool more = it < end;
        if (more) {
            d = item_decode(it, h0, h0inv);
            dq_load(v, zs, d, lane, g, pol);
        }
        dq_signal(dc, lane);
        if (!more) break;
    }
}
__device__ __forceinline__ void dq_bulk_zs(uint32_t (&zs)[16], const DqItem& d, int lane, const DqPtrs& g) {
    if (d.kv == 0) {
        const int so = (d.head * NGK + d.tok / GRP) * DH + 4 * lane;
        const uint2 zz = __ldg(reinterpret_cast<const uint2*>(g.kz + so)), ss = __ldg(reinterpret_cast<const uint2*>(g.ks + so));
        zs[0] = zz.x; zs[1] = zz.y; zs[2] = ss.x; zs[3] = ss.y;
    } else {
        const uint4* z = reinterpret_cast<const uint4*>(g.vz + d.head * SEQ + d.tok);
        const uint4* s = reinterpret_cast<const uint4*>(g.vs + d.head * SEQ + d.tok);
        const uint4 z0 = __ldg(z), z1 = __ldg(z + 1), s0 = __ldg(s), s1 = __ldg(s + 1);
        zs[0] = z0.x; zs[1] = z0.y; zs[2] = z0.z; zs[3] = z0.w; zs[4] = z1.x; zs[5] = z1.y; zs[6] = z1.z; zs[7] = z1.w;
        zs[8] = s0.x; zs[9] = s0.y; zs[10] = s0.z; zs[11] = s0.w; zs[12] = s1.x; zs[13] = s1.y; zs[14] = s1.z; zs[15] = s1.w;
    }
}
__device__ __forceinline__ void dq_bulk_convert(const int (&v)[64], const uint32_t (&zs)[16], int kv, uint32_t dst, int lane) {
    if (kv == 0) {
        uint32_t h0, l0, h1, l1;
        k_scale_split(zs[2], h0, l0); k_scale_split(zs[3], h1, l1);
        const uint32_t a = dst + (lane >> 4) * 2048 + (lane & 1) * 8;
        const int ch = (lane & 15) >> 1;
#pragma unroll
        for (int r = 0; r < 16; r++)
            asm volatile("st.shared.v2.u32 [%0], {%1, %2};" ::"r"(a + r * 128 + ((ch ^ (r & 7)) << 4)),
                         "r"(dq_k(v[4 * r], v[4 * r + 1], zs[0], h0, l0)), "r"(dq_k(v[4 * r + 2], v[4 * r + 3], zs[1], h1, l1)) : "memory");
    } else {
        const int i = lane >> 3, c = (lane & 7) >> 1, ch = 4 * (i & 1) + 2 * (lane & 1);
        const uint32_t a = dst + (i >> 1) * 2048 + 4 * c;
#pragma unroll
        for (int r = 0; r < 16; r++) {
            const uint32_t sel = (r & 1) ? 0x3232u : 0x1010u;
            const uint32_t z = __byte_perm(zs[r >> 1], 0, sel), s = __byte_perm(zs[8 + (r >> 1)], 0, sel);
            asm volatile("st.shared.u32 [%0], %1;" ::"r"(a + r * 128 + ((ch ^ (r & 7)) << 4)), "r"(dq_v(v[4 * r], v[4 * r + 1], z, s)) : "memory");
            asm volatile("st.shared.u32 [%0], %1;" ::"r"(a + r * 128 + (((ch + 1) ^ (r & 7)) << 4)), "r"(dq_v(v[4 * r + 2], v[4 * r + 3], z, s)) : "memory");
        }
    }
}

template <int V> struct IC { static constexpr int value = V; };
struct Ring {
    uint32_t slot, phase, desc;
    __device__ __forceinline__ void advance() {
        slot += 1; desc += STAGE_BYTES >> 4;
        if (slot == NST) { slot = 0; desc -= NST * (STAGE_BYTES >> 4); phase ^= 1; }
    }
};

__device__ __forceinline__ void load_q(uint32_t (&qf)[32], uint32_t qrow, uint32_t qsw) {
#pragma unroll
    for (int kk = 0; kk < 8; kk++)
        asm volatile("ldmatrix.sync.aligned.m8n8.x4.shared.b16 {%0, %1, %2, %3}, [%4];"
                     : "=r"(qf[4 * kk]), "=r"(qf[4 * kk + 1]), "=r"(qf[4 * kk + 2]), "=r"(qf[4 * kk + 3])
                     : "r"(qrow + (kk >> 2) * (QBUF_BYTES / 2) + (qsw ^ ((kk & 3) << 5))) : "memory");
}
__device__ __forceinline__ uint32_t tile_desc(uint32_t addr) { return (addr & 0x3FFFFu) >> 4; }
__device__ __forceinline__ uint32_t k_desc(uint32_t d) { return d | (1u << 16); }
__device__ __forceinline__ uint32_t v_desc(uint32_t d) { return d | (1024u << 16); }
__device__ __forceinline__ void issue_qk(float (&S)[64], const uint32_t (&qf)[32], uint32_t lo) {
    const uint64_t hi = (uint64_t)(64u | (1u << 30)) << 32;
#pragma unroll
    for (int kk = 0; kk < 8; kk++)
        wgmma_rs<0>(S, qf[4 * kk], qf[4 * kk + 1], qf[4 * kk + 2], qf[4 * kk + 3],
                    hi | (uint64_t)(lo + (kk >> 2) * 1024 + (kk & 3) * 2), kk != 0);
}
__device__ __forceinline__ void issue_pv(float (&O)[64], const uint32_t (&P)[32], uint32_t lo, int acc) {
    const uint64_t hi = (uint64_t)(64u | (1u << 30)) << 32;
#pragma unroll
    for (int kk = 0; kk < 8; kk++)
        wgmma_rs<1>(O, P[4 * kk], P[4 * kk + 1], P[4 * kk + 2], P[4 * kk + 3], hi | (uint64_t)(lo + kk * 128), kk != 0 ? 1 : acc);
}
template <int J0, int J1>
__device__ __forceinline__ void exp_part(float (&S)[64], float (&acc)[4]) {
#pragma unroll
    for (int j = J0; j < J1; j++) {
        S[4 * j + 0] = ex2(S[4 * j + 0]);
        S[4 * j + 1] = ex2(S[4 * j + 1]);
        S[4 * j + 2] = ex2(S[4 * j + 2]);
        S[4 * j + 3] = ex2(S[4 * j + 3]);
        if (j == 0) { acc[0] = S[0]; acc[1] = S[1]; acc[2] = S[2]; acc[3] = S[3]; }
        else { acc[0] += S[4 * j + 0]; acc[1] += S[4 * j + 1]; acc[2] += S[4 * j + 2]; acc[3] += S[4 * j + 3]; }
    }
}
__device__ __forceinline__ void cvt_p(const float (&S)[64], uint32_t (&P)[32]) {
#pragma unroll
    for (int j = 0; j < 16; j++) {
        P[2 * j] = pack_bf16(S[4 * j], S[4 * j + 1]);
        P[2 * j + 1] = pack_bf16(S[4 * j + 2], S[4 * j + 3]);
    }
}
__device__ __forceinline__ bool finish_l(float l0, float l1, float& i0, float& i1) {
    l0 += __shfl_xor_sync(0xffffffffu, l0, 1); l1 += __shfl_xor_sync(0xffffffffu, l1, 1);
    l0 += __shfl_xor_sync(0xffffffffu, l0, 2); l1 += __shfl_xor_sync(0xffffffffu, l1, 2);
    asm("rcp.approx.ftz.f32 %0, %1;" : "=f"(i0) : "f"(l0));
    asm("rcp.approx.ftz.f32 %0, %1;" : "=f"(i1) : "f"(l1));
    return l0 >= L_MIN && l0 <= L_MAX && l1 >= L_MIN && l1 <= L_MAX;
}
__device__ __forceinline__ bool store_o(const float (&O)[64], float i0, float i1, __nv_bfloat16* __restrict__ orow) {
    float c0 = 0.f, c1 = 0.f, c2 = 0.f, c3 = 0.f;
#pragma unroll
    for (int i = 0; i < 4; i++) {
        uint4 a, b;
        a.x = pack_bf16(O[16 * i + 0] * i0, O[16 * i + 1] * i0);
        a.y = pack_bf16(O[16 * i + 4] * i0, O[16 * i + 5] * i0);
        a.z = pack_bf16(O[16 * i + 8] * i0, O[16 * i + 9] * i0);
        a.w = pack_bf16(O[16 * i + 12] * i0, O[16 * i + 13] * i0);
        b.x = pack_bf16(O[16 * i + 2] * i1, O[16 * i + 3] * i1);
        b.y = pack_bf16(O[16 * i + 6] * i1, O[16 * i + 7] * i1);
        b.z = pack_bf16(O[16 * i + 10] * i1, O[16 * i + 11] * i1);
        b.w = pack_bf16(O[16 * i + 14] * i1, O[16 * i + 15] * i1);
        *reinterpret_cast<uint4*>(orow + 32 * i) = a;
        *reinterpret_cast<uint4*>(orow + 8 * DH + 32 * i) = b;
#pragma unroll
        for (int e = 0; e < 16; e += 4) {
            c0 = fmaf(O[16 * i + e], 0.f, c0); c1 = fmaf(O[16 * i + e + 1], 0.f, c1);
            c2 = fmaf(O[16 * i + e + 2], 0.f, c2); c3 = fmaf(O[16 * i + e + 3], 0.f, c3);
        }
    }
    return (c0 + c1) + (c2 + c3) == 0.f;
}

struct Sched {
    int rem;
    int nlight;
    int bulk;
    int h0, h0inv;
    int nhelp;
    int nfirst;
};

__global__ void __cluster_dims__(2, 1, 1) __launch_bounds__(384, 1)
attn_kernel(const __grid_constant__ CUtensorMap qmap, const int* __restrict__ qk, const int* __restrict__ qv,
            const __nv_bfloat16* __restrict__ ks, const __nv_bfloat16* __restrict__ kz,
            const __nv_bfloat16* __restrict__ vs, const __nv_bfloat16* __restrict__ vz,
            __nv_bfloat16* __restrict__ out, const Sched sc) {
    extern __shared__ __align__(1024) uint8_t smem_raw[];
    const uint32_t sb = smem_u32(smem_raw);
    const uint32_t qbuf = sb + NS * TILE_BYTES;
    const uint32_t bar_full = qbuf + QBUF_BYTES, bar_empty = bar_full + 8 * NS;
    const uint32_t bar_qfull = bar_empty + 8 * NS, bar_qempty = bar_qfull + 8, pin_addr = bar_qempty + 8;
    const uint32_t bar_bempty = pin_addr + 8;
    const uint32_t bar_rfull = bar_bempty + 8 * NIN, bar_rempty = bar_rfull + 16;
    const uint32_t bar_bfull = bar_rempty + 16, bar_bdone = bar_bfull + 8 * MAX_CHUNKS_PER_CTA;
    volatile uint8_t* redo = smem_raw + NS * TILE_BYTES + QBUF_BYTES + 1024;
    const int wg = __shfl_sync(0xffffffffu, threadIdx.x >> 7, 0);
    const int warp = __shfl_sync(0xffffffffu, (threadIdx.x >> 5) & 3, 0);
    const int lane = threadIdx.x & 31;
    uint32_t rank; asm("mov.u32 %0, %%cluster_ctarank;" : "=r"(rank));
    const int cluster_id = blockIdx.x >> 1, nclusters = gridDim.x >> 1;

    const bool light = sc.bulk && cluster_id >= sc.rem;
    const int h0 = sc.h0, h0inv = sc.h0inv;
    const int chunk0 = sc.nfirst / ITEMS_PER_CHUNK + (int)blockIdx.x - 2 * sc.rem, chunk_stride = 2 * sc.nlight;
    const int nchunks = light ? (NCHUNKS - chunk0 + chunk_stride - 1) / chunk_stride : 0;
    const DqPtrs dq{qk, qv, ks, kz, vs, vz};
    uint64_t pol;
    asm volatile("createpolicy.fractional.L2::evict_first.b64 %0, 1.0;" : "=l"(pol));
    const int gwarp = wg * 4 + warp;

    if (gwarp == 0) {
        if (sb & 1023u) __trap();
        if (lane < NST) { mbar_init(bar_full + 8 * lane, 1); mbar_init(bar_empty + 8 * lane, 4); }
        if (lane == 8) { mbar_init(bar_qfull, 1); mbar_init(bar_qempty, 8); }
        if (lane == 9 || lane == 10) { mbar_init(bar_rfull + 8 * (lane - 9), 1); mbar_init(bar_rempty + 8 * (lane - 9), 2); }
        if (light) {
            if (lane >= 16 && lane < 16 + NIN) mbar_init(bar_bempty + 8 * (lane - 16), 4);
            for (int s = lane; s < nchunks; s += 32) { mbar_init(bar_bfull + 8 * s, 1); mbar_init(bar_bdone + 8 * s, 4); }
        }
        asm volatile("fence.mbarrier_init.release.cluster;\nfence.acq_rel.cta;" ::: "memory");
        __syncwarp();
        if (lane == 0) {
            mbar_expect_tx(bar_qfull, QBUF_BYTES);
            tma_load_2d(qbuf, &qmap, 0, cluster_id * 256 + rank * 128, bar_qfull);
            tma_load_2d(qbuf + QBUF_BYTES / 2, &qmap, 64, cluster_id * 256 + rank * 128, bar_qfull);
        }
        __syncwarp();
        cluster_arrive();
        if (light) {
            if (lane == 0) {
                const long long t0 = clock64();
                while (clock64() - t0 < LOADER_DELAY) {}
                for (int k = 0; k < nchunks; k++) {
                    const int slot = k % NIN;
                    const DqItem d = item_decode((chunk0 + k * chunk_stride) * ITEMS_PER_CHUNK, h0, h0inv);
                    mbar_wait(bar_bempty + 8 * slot, ((k / NIN) & 1) ^ 1);
                    mbar_expect_tx(bar_bfull + 8 * k, TILE_BYTES);
                    bulk_load_hint(sb + slot * TILE_BYTES, (d.kv ? qv : qk) + (size_t)(d.head * SEQ + d.tok) * DH, TILE_BYTES, bar_bfull + 8 * k, pol);
                }
            }
            __syncwarp();
        }
        cluster_wait();
    } else {
        cluster_arrive();
        if (light || wg != 0) cluster_wait();
        if (light && gwarp == 1) {
            if (lane == 0) {
                for (int sig = 0; sig < nchunks;) {
                    mbar_wait(bar_bdone + 8 * sig, 0);
                    int m = 1;
                    while (m < 4 && sig + m < nchunks && mbar_test(bar_bdone + 8 * (sig + m), 0)) m++;
                    asm volatile("fence.acq_rel.gpu;" ::: "memory");
                    for (int i = 0; i < m; i++) {
                        const DqItem d = item_decode((chunk0 + (sig + i) * chunk_stride) * ITEMS_PER_CHUNK, h0, h0inv);
                        asm volatile("red.relaxed.gpu.global.add.u32 [%0], %1;" ::"l"(g_cnt + d.head * UNITS_PER_HEAD + d.p), "r"(ITEMS_PER_CHUNK) : "memory");
                    }
                    sig += m;
                }
            }
            __syncwarp();
        } else if (light) {
            const uint32_t obuf = sb + NIN * TILE_BYTES + (gwarp - 2) * 4096;
            int j = gwarp - 2, kprev = -1;
            DqItem d;
            uint32_t zs[16];
            if (j < 4 * nchunks) { d = item_decode((chunk0 + (j >> 2) * chunk_stride) * ITEMS_PER_CHUNK + (j & 3) * 4, h0, h0inv); dq_bulk_zs(zs, d, lane, dq); }
            while (j < 4 * nchunks) {
                const int k = j >> 2, slot = k % NIN;
                mbar_wait(bar_bfull + 8 * k, 0);
                int v[64];
                const uint32_t src = sb + slot * TILE_BYTES + (j & 3) * 8192 + lane * 16;
#pragma unroll
                for (int r = 0; r < 16; r++)
                    asm volatile("ld.shared.v4.s32 {%0, %1, %2, %3}, [%4];" : "=r"(v[4 * r]), "=r"(v[4 * r + 1]), "=r"(v[4 * r + 2]), "=r"(v[4 * r + 3])
                                 : "r"(src + r * 512) : "memory");
                __syncwarp();
                if (lane == 0) {
                    mbar_arrive(bar_bempty + 8 * slot);
                    if (kprev >= 0) {
                        asm volatile("cp.async.bulk.wait_group 0;" ::: "memory");
                        mbar_arrive(bar_bdone + 8 * kprev);
                    }
                }
                __syncwarp();
                dq_bulk_convert(v, zs, d.kv, obuf, lane);
                asm volatile("fence.proxy.async.shared::cta;" ::: "memory");
                __syncwarp();
                if (lane == 0) {
                    uint8_t* o = kv_tile(d.kv, d.head, d.tok / BN) + (d.tok % BN) * 128;
                    bulk_store(o, obuf, 2048);
                    bulk_store(o + TILE_BYTES / 2, obuf + 2048, 2048);
                    asm volatile("cp.async.bulk.commit_group;" ::: "memory");
                }
                kprev = k;
                j += 10;
                if (j < 4 * nchunks) { d = item_decode((chunk0 + (j >> 2) * chunk_stride) * ITEMS_PER_CHUNK + (j & 3) * 4, h0, h0inv); dq_bulk_zs(zs, d, lane, dq); }
            }
            if (kprev >= 0 && lane == 0) {
                asm volatile("cp.async.bulk.wait_group 0;" ::: "memory");
                mbar_arrive(bar_bdone + 8 * kprev);
            }
            __syncwarp();
        }
    }
    if (light) { cluster_arrive_release(); cluster_wait(); }

    if (wg == 0) {
        asm volatile("setmaxnreg.dec.sync.aligned.u32 56;");
        if (warp == 0) {
            uint32_t qphase = 0;
            auto load_qtile = [&](int t) {
                if (lane == 0) {
                    mbar_wait(bar_qempty, qphase);
                    mbar_expect_tx(bar_qfull, QBUF_BYTES);
                    tma_load_2d(qbuf, &qmap, 0, t * 256 + rank * 128, bar_qfull);
                    tma_load_2d(qbuf + QBUF_BYTES / 2, &qmap, 64, t * 256 + rank * 128, bar_qfull);
                }
                __syncwarp();
                qphase ^= 1;
            };
            Ring r{0, 1, 0};
            int vhead = -1;
            uint32_t vmask = 0;
            auto await_unit = [&](int kv, int head, int blk) {
                const int p = kv == 0 ? (blk == 0 ? 0 : 2 * blk - 1) : (blk == NBLK - 1 ? UNITS_PER_HEAD - 1 : 2 * blk + 2);
                if (head != vhead) { vhead = head; vmask = 0; }
                if (!((vmask >> p) & 1)) {
                    uint32_t n = 0;
                    while (true) {
                        unsigned int c;
                        asm volatile("ld.acquire.gpu.global.u32 %0, [%1];" : "=r"(c) : "l"(g_cnt + head * UNITS_PER_HEAD + lane) : "memory");
                        vmask = __ballot_sync(0xffffffffu, c == ITEMS_PER_UNIT);
                        if ((vmask >> p) & 1) break;
                        if (++n > (1u << 22)) __trap();
                    }
                    asm volatile("fence.proxy.async.global;" ::: "memory");
                }
            };
            auto load = [&](int khead, int kblk, int vh, int vblk) {
                if (vh >= 0) await_unit(1, vh, vblk);
                if (khead >= 0) await_unit(0, khead, kblk);
                if (lane == 0) {
                    const uint32_t full = bar_full + 8 * r.slot, dst = sb + r.slot * STAGE_BYTES + rank * (TILE_BYTES / 2);
                    mbar_wait(bar_empty + 8 * r.slot, r.phase);
                    mbar_expect_tx(full, (khead >= 0 ? TILE_BYTES : 0) + (vh >= 0 ? TILE_BYTES : 0));
                    if (khead >= 0) bulk_load_mc(dst, kv_tile(0, khead, kblk) + rank * (TILE_BYTES / 2), TILE_BYTES / 2, full, (uint16_t)3);
                    if (vh >= 0) bulk_load_mc(dst + TILE_BYTES, kv_tile(1, vh, vblk) + rank * (TILE_BYTES / 2), TILE_BYTES / 2, full, (uint16_t)3);
                }
                __syncwarp();
                r.advance();
            };
            load(cluster_id / TILES_PER_HEAD, 0, -1, 0);
            for (int t = cluster_id; t < NTILES; t += nclusters) {
                const int head = t / TILES_PER_HEAD;
                const int tn = t + nclusters;
                for (int j = 0; j < NBLK; j++) {
                    if (j == 4 && tn < NTILES) load_qtile(tn);
                    if (j < NBLK - 1) load(head, j + 1, head, j);
                    else load(tn < NTILES ? tn / TILES_PER_HEAD : -1, 0, head, j);
                }
            }
            if (lane == 0) {
                const unsigned int prev = atomicAdd(&g_done, 1u);
                if (prev == gridDim.x - 1) {
                    for (int i = 0; i < HKV * UNITS_PER_HEAD; i++) g_cnt[i] = 0;
                    g_done = 0;
                }
            }
            __syncwarp();
            bar_sync(3, 288);
            uint32_t n = 0;
            for (int t = cluster_id, k = 0; t < NTILES; t += nclusters, k++) {
                if (!redo[k]) continue;
                load_qtile(t);
                if (lane == 0) {
                    for (int j = 0; j < 2 * NBLK; j++, n++) {
                        const uint32_t s = n & 1;
                        mbar_wait(bar_rempty + 8 * s, ((n >> 1) & 1) ^ 1);
                        mbar_expect_tx(bar_rfull + 8 * s, TILE_BYTES);
                        bulk_load(sb + s * TILE_BYTES, kv_tile(j & 1, t / TILES_PER_HEAD, j >> 1), TILE_BYTES, bar_rfull + 8 * s);
                    }
                }
                __syncwarp();
            }
        } else {
            if (!light) {
                dequant_loop(blockIdx.x * 3 + (warp - 1), sc.nhelp, sc.nfirst, h0, h0inv, lane, dq, pol);
                cluster_wait();
            }
        }
        cluster_arrive(); cluster_wait();
    } else {
        asm volatile("setmaxnreg.inc.sync.aligned.u32 224;");
        const int w = wg - 1;
        const int my_bar = 1 + w, other_bar = 2 - w;
        const int row_in_tile = rank * 128 + w * 64 + warp * 16 + (lane >> 2);
        const int coff = (lane & 3) * 8;
        const uint32_t qrow = qbuf + (w * 64 + warp * 16 + (lane & 15)) * 128;
        const uint32_t qsw = ((lane >> 4) ^ (lane & 7)) << 4;
        const uint32_t rem_empty = mapa(bar_empty, warp & 1);
        const bool releaser = lane == 0 && warp < 2;
        uint32_t qf[32], P[32];
        float S[64], O[64];
        float l0 = 0.f, l1 = 0.f, lo0 = 1.f, lo1 = 1.f;
        uint32_t qphase = 0;
        Ring r{0, 0, tile_desc(sb)};
        auto release = [&]() {
            if (releaser) mbar_arrive_remote(rem_empty + 8 * r.slot);
            r.advance();
        };
        auto reload_q = [&]() {
            mbar_wait(bar_qfull, qphase);
            qphase ^= 1;
            load_q(qf, qrow, qsw);
            __syncwarp();
            if (lane == 0) mbar_arrive(bar_qempty);
        };
        auto pin = [&](float x) {
            asm volatile("{\n.reg .pred p;\nsetp.eq.f32 p, %0, 0fBF800000;\n@p st.shared.f32 [%1], %0;\n}\n" ::"f"(x), "r"(pin_addr) : "memory");
        };
        int t = cluster_id, tk = 0;
#pragma unroll
        for (int i = 0; i < 64; i++) { S[i] = 0.f; O[i] = 0.f; }
        if (gwarp == 4) { reinterpret_cast<volatile uint32_t*>(redo)[lane] = 0; reinterpret_cast<volatile uint32_t*>(redo)[lane + 32] = 0; }
        if (w == 1) bar_arrive(1, 256);
        reload_q();
        {
            mbar_wait(bar_full, 0);
            bar_sync(my_bar, 256);
            wg_fence();
            issue_qk(S, qf, k_desc(r.desc));
            wg_commit();
            bar_arrive(other_bar, 256);
            wg_wait<0>();
            fence_regs(S);
            release();
            float acc[4];
            exp_part<0, 16>(S, acc);
            l0 = acc[0] + acc[1]; l1 = acc[2] + acc[3];
            cvt_p(S, P);
        }
        uint32_t ready = 0;
        auto step = [&](auto first, bool store_prev, __nv_bfloat16* orow, bool swap_l, bool new_q) {
            constexpr bool FIRST = decltype(first)::value;
            if (!ready) mbar_wait(bar_full + 8 * r.slot, r.phase);
            bar_sync(my_bar, 256);
            wg_fence();
            issue_qk(S, qf, k_desc(r.desc));
            wg_commit();
            if (FIRST) {
                if (store_prev) {
                    float i0, i1;
                    const bool ok = finish_l(lo0, lo1, i0, i1);
                    if (!store_o(O, i0, i1, orow) || !ok) redo[tk - 1] = 1;
                }
                fence_regs(O);
                wg_fence();
            }
            issue_pv(O, P, v_desc(r.desc + (TILE_BYTES >> 4)), !FIRST);
            wg_commit();
            bar_arrive(other_bar, 256);
            wg_wait<1>();
            fence_regs(S);
            if (!FIRST && new_q) { fence_regs(qf); reload_q(); }
            float acc[4];
            exp_part<0, PIN_J>(S, acc);
            pin((acc[0] + acc[1]) + (acc[2] + acc[3]));
            wg_wait<0>();
            fence_regs(O);
            fence_regs(P);
            release();
            ready = mbar_test(bar_full + 8 * r.slot, r.phase);
            exp_part<PIN_J, 16>(S, acc);
            cvt_p(S, P);
            if (!FIRST && swap_l) { lo0 = l0; lo1 = l1; l0 = 0.f; l1 = 0.f; }
            l0 += acc[0] + acc[1]; l1 += acc[2] + acc[3];
        };
        __nv_bfloat16* oprev = out;
        while (true) {
            const int tn = t + nclusters;
            const bool has_next = tn < NTILES;
            step(IC<1>{}, tk > 0, oprev, false, false);
            const int jend = has_next ? NBLK : NBLK - 1;
#pragma unroll 1
            for (int j = 1; j < jend; j++) step(IC<0>{}, false, nullptr, j == NBLK - 1, has_next && j == NBLK - 2);
            oprev = out + (size_t)(t * 256 + row_in_tile) * DH + coff;
            if (has_next) {
                t = tn; tk++;
            } else {
                mbar_wait(bar_full + 8 * r.slot, r.phase);
                bar_sync(my_bar, 256);
                wg_fence();
                issue_pv(O, P, v_desc(r.desc + (TILE_BYTES >> 4)), 1);
                wg_commit();
                if (w == 0) bar_arrive(other_bar, 256);
                wg_wait<0>();
                fence_regs(O);
                float i0, i1;
                const bool ok = finish_l(l0, l1, i0, i1);
                if (!store_o(O, i0, i1, oprev) || !ok) redo[tk] = 1;
                break;
            }
        }
        bar_sync(3, 288);
        uint32_t n = 0;
        for (int tt = cluster_id, k = 0; tt < NTILES; tt += nclusters, k++) {
            if (!redo[k]) continue;
            mbar_wait(bar_qfull, qphase);
            qphase ^= 1;
            float m0 = -INFINITY, m1 = -INFINITY;
            l0 = 0.f; l1 = 0.f;
#pragma unroll 1
            for (int j = 0; j < NBLK; j++) {
                load_q(qf, qrow, qsw);
                mbar_wait(bar_rfull + 8 * (n & 1), (n >> 1) & 1);
                wg_fence();
                issue_qk(S, qf, k_desc(tile_desc(sb + (n & 1) * TILE_BYTES)));
                wg_commit();
                wg_wait<0>();
                fence_regs(S);
                if (warp == 0 && lane == 0) mbar_arrive(bar_rempty + 8 * (n & 1));
                n++;
                float a0 = m0, a1 = m1;
#pragma unroll
                for (int i = 0; i < 16; i++) {
                    a0 = fmaxf(a0, fmaxf(S[4 * i], S[4 * i + 1]));
                    a1 = fmaxf(a1, fmaxf(S[4 * i + 2], S[4 * i + 3]));
                }
                a0 = fmaxf(a0, __shfl_xor_sync(0xffffffffu, a0, 1)); a1 = fmaxf(a1, __shfl_xor_sync(0xffffffffu, a1, 1));
                a0 = fmaxf(a0, __shfl_xor_sync(0xffffffffu, a0, 2)); a1 = fmaxf(a1, __shfl_xor_sync(0xffffffffu, a1, 2));
                const float al0 = ex2(m0 - a0), al1 = ex2(m1 - a1);
                m0 = a0; m1 = a1;
#pragma unroll
                for (int i = 0; i < 16; i++) {
                    S[4 * i] -= a0; S[4 * i + 1] -= a0; S[4 * i + 2] -= a1; S[4 * i + 3] -= a1;
                    O[4 * i] *= al0; O[4 * i + 1] *= al0; O[4 * i + 2] *= al1; O[4 * i + 3] *= al1;
                }
                float acc[4];
                exp_part<0, 16>(S, acc);
                l0 = l0 * al0 + (acc[0] + acc[1]); l1 = l1 * al1 + (acc[2] + acc[3]);
                cvt_p(S, P);
                mbar_wait(bar_rfull + 8 * (n & 1), (n >> 1) & 1);
                wg_fence();
                issue_pv(O, P, v_desc(tile_desc(sb + (n & 1) * TILE_BYTES)), j != 0);
                wg_commit();
                wg_wait<0>();
                fence_regs(O);
                if (warp == 0 && lane == 0) mbar_arrive(bar_rempty + 8 * (n & 1));
                n++;
            }
            __syncwarp();
            if (lane == 0) mbar_arrive(bar_qempty);
            {
                float i0, i1;
                finish_l(l0, l1, i0, i1);
                store_o(O, i0, i1, out + (size_t)(tt * 256 + row_in_tile) * DH + coff);
            }
        }
        cluster_arrive(); cluster_wait();
    }
}

}

extern "C" void kernel_launch(void* const* d_in, const int* in_sizes, int n_in, void* d_out, int out_size) {
    const __nv_bfloat16* q = (const __nv_bfloat16*)d_in[0];
    const int* qk = (const int*)d_in[1];
    const int* qv = (const int*)d_in[2];
    const __nv_bfloat16* ks = (const __nv_bfloat16*)d_in[3];
    const __nv_bfloat16* kz = (const __nv_bfloat16*)d_in[4];
    const __nv_bfloat16* vs = (const __nv_bfloat16*)d_in[5];
    const __nv_bfloat16* vz = (const __nv_bfloat16*)d_in[6];
    typedef CUresult (*EncodeFn)(CUtensorMap*, CUtensorMapDataType, cuuint32_t, void*, const cuuint64_t*, const cuuint64_t*,
                                 const cuuint32_t*, const cuuint32_t*, CUtensorMapInterleave, CUtensorMapSwizzle,
                                 CUtensorMapL2promotion, CUtensorMapFloatOOBfill);
    static EncodeFn encode = nullptr;
    static int grid = 0;
    static Sched sc;
    if (grid == 0) {
        void* fn = nullptr;
        cudaDriverEntryPointQueryResult qr;
        cudaGetDriverEntryPoint("cuTensorMapEncodeTiled", &fn, cudaEnableDefault, &qr);
        encode = (EncodeFn)fn;
        cudaFuncSetAttribute(attn_kernel, cudaFuncAttributeMaxDynamicSharedMemorySize, SMEM_BYTES);
        cudaLaunchConfig_t cfg = {};
        cfg.gridDim = dim3(2, 1, 1); cfg.blockDim = dim3(384, 1, 1); cfg.dynamicSmemBytes = SMEM_BYTES;
        cudaLaunchAttribute at[1];
        at[0].id = cudaLaunchAttributeClusterDimension;
        at[0].val.clusterDim.x = 2; at[0].val.clusterDim.y = 1; at[0].val.clusterDim.z = 1;
        cfg.attrs = at; cfg.numAttrs = 1;
        int nc = 0;
        if (cudaOccupancyMaxActiveClusters(&nc, attn_kernel, &cfg) != cudaSuccess || nc <= 0) { nc = 1; (void)cudaGetLastError(); }
        if (nc > NTILES) nc = NTILES;
        if (FORCE_CLUSTERS) nc = FORCE_CLUSTERS;
        sc.rem = NTILES % nc;
        sc.nlight = sc.rem ? nc - sc.rem : 0;
        sc.bulk = sc.nlight >= MIN_LIGHT;
        const int lead = sc.bulk ? sc.rem : nc;
        sc.h0 = (lead + TILES_PER_HEAD - 1) / TILES_PER_HEAD;
        if (sc.h0 > HKV) sc.h0 = HKV;
        sc.h0inv = (65536 + sc.h0 - 1) / sc.h0;
        sc.nhelp = 2 * lead * 3;
        sc.nfirst = NITEMS;
        if (sc.bulk && ((sc.nhelp * NFIRST) & ~(ITEMS_PER_CHUNK - 1)) < NITEMS) sc.nfirst = (sc.nhelp * NFIRST) & ~(ITEMS_PER_CHUNK - 1);
        grid = nc * 2;
    }
    CUtensorMap qmap;
    const cuuint64_t dims[2] = {(cuuint64_t)DH, (cuuint64_t)HQ * SEQ};
    const cuuint64_t strides[1] = {(cuuint64_t)DH * 2};
    const cuuint32_t box[2] = {64, 128};
    const cuuint32_t estr[2] = {1, 1};
    encode(&qmap, CU_TENSOR_MAP_DATA_TYPE_BFLOAT16, 2, (void*)q, dims, strides, box, estr, CU_TENSOR_MAP_INTERLEAVE_NONE,
           CU_TENSOR_MAP_SWIZZLE_128B, CU_TENSOR_MAP_L2_PROMOTION_L2_128B, CU_TENSOR_MAP_FLOAT_OOB_FILL_NONE);
    attn_kernel<<<grid, 384, SMEM_BYTES>>>(qmap, qk, qv, ks, kz, vs, vz, (__nv_bfloat16*)d_out, sc);
}
```

```cpp
#include <cuda_runtime.h>
#include <cuda_bf16.h>
#include <cuda.h>
#include <stdint.h>

#define PIN_J 7
#define LOADER_DELAY 2000
#define Q_AFTER 1
#define NFIRST 3
#define FORCE_CLUSTERS 0

namespace {

constexpr int HQ = 32, HKV = 8, SEQ = 2048, DH = 128, NGK = 2, GRP = SEQ / NGK;
constexpr int BN = 128, NBLK = SEQ / BN;
constexpr int TILE_BYTES = BN * DH * 2;
constexpr int NS = 6;
constexpr int NST = NS / 2;
constexpr int STAGE_BYTES = 2 * TILE_BYTES;
constexpr int NTILES = HQ * SEQ / 256;
constexpr int TILES_PER_HEAD = NTILES / HKV;
constexpr int QBUF_BYTES = 128 * DH * 2;
constexpr int SMEM_BYTES = NS * TILE_BYTES + QBUF_BYTES + 2048;
constexpr int UNITS_PER_HEAD = 2 * NBLK;
constexpr int ITEMS_PER_UNIT = 32;
constexpr int NITEMS = HKV * UNITS_PER_HEAD * ITEMS_PER_UNIT;
constexpr int ITEMS_PER_CHUNK = 16;
constexpr int NCHUNKS = NITEMS / ITEMS_PER_CHUNK;
constexpr int MIN_LIGHT = 6;
constexpr int MAX_CHUNKS_PER_CTA = (NCHUNKS + 2 * MIN_LIGHT - 1) / (2 * MIN_LIGHT);
constexpr int NIN = 4;
constexpr float SCALE_LOG2 = 0.08838834764831845f * 1.4426950408889634f;
constexpr float L_MIN = 9.094947017729282e-13f, L_MAX = 1099511627776.0f;

__device__ __align__(1024) uint4 g_kv[2 * HKV * NBLK * (TILE_BYTES / 16)];
__device__ __align__(128) unsigned int g_cnt[HKV * UNITS_PER_HEAD];
__device__ unsigned int g_done;

__device__ __forceinline__ uint32_t smem_u32(const void* p) { return (uint32_t)__cvta_generic_to_shared(p); }

__device__ __forceinline__ uint4 ld_shared_v4(uint32_t a) {
    uint4 r;
    asm volatile("ld.shared.v4.u32 {%0, %1, %2, %3}, [%4];" : "=r"(r.x), "=r"(r.y), "=r"(r.z), "=r"(r.w) : "r"(a) : "memory");
    return r;
}
__device__ __forceinline__ void mbar_init(uint32_t a, uint32_t cnt) {
    asm volatile("mbarrier.init.shared::cta.b64 [%0], %1;" ::"r"(a), "r"(cnt) : "memory");
}
__device__ __forceinline__ void mbar_expect_tx(uint32_t a, uint32_t bytes) {
    asm volatile("mbarrier.arrive.expect_tx.shared::cta.b64 _, [%0], %1;" ::"r"(a), "r"(bytes) : "memory");
}
__device__ __forceinline__ void mbar_wait(uint32_t a, uint32_t parity) {
    asm volatile(
        "{\n"
        ".reg .pred p;\n"
        ".reg .u32 n;\n"
        "mbarrier.try_wait.parity.shared::cta.b64 p, [%0], %1;\n"
        "@p bra WAIT_DONE;\n"
        "mov.u32 n, 0;\n"
        "WAIT_LOOP:\n"
        "mbarrier.try_wait.parity.shared::cta.b64 p, [%0], %1;\n"
        "@p bra WAIT_DONE;\n"
        "add.u32 n, n, 1;\n"
        "setp.lt.u32 p, n, 0x1000000;\n"
        "@p bra WAIT_LOOP;\n"
        "trap;\n"
        "WAIT_DONE:\n"
        "}\n" ::"r"(a), "r"(parity) : "memory");
}
__device__ __forceinline__ void mbar_wait_sleep(uint32_t a, uint32_t parity) {
    asm volatile(
        "{\n"
        ".reg .pred p;\n"
        ".reg .u32 n;\n"
        "mov.u32 n, 0;\n"
        "WAIT_LOOP:\n"
        "mbarrier.try_wait.parity.shared::cta.b64 p, [%0], %1, 4000;\n"
        "@p bra WAIT_DONE;\n"
        "add.u32 n, n, 1;\n"
        "setp.lt.u32 p, n, 0x100000;\n"
        "@p bra WAIT_LOOP;\n"
        "trap;\n"
        "WAIT_DONE:\n"
        "}\n" ::"r"(a), "r"(parity) : "memory");
}
__device__ __forceinline__ uint32_t mbar_test(uint32_t a, uint32_t parity) {
    uint32_t ok;
    asm volatile("{\n.reg .pred p;\nmbarrier.test_wait.parity.shared::cta.b64 p, [%1], %2;\nselp.u32 %0, 1, 0, p;\n}\n"
                 : "=r"(ok) : "r"(a), "r"(parity) : "memory");
    return ok;
}
__device__ __forceinline__ void mbar_arrive(uint32_t a) {
    asm volatile("mbarrier.arrive.shared::cta.b64 _, [%0];" ::"r"(a) : "memory");
}
__device__ __forceinline__ uint32_t mapa(uint32_t a, uint32_t cta) {
    uint32_t r; asm("mapa.shared::cluster.u32 %0, %1, %2;" : "=r"(r) : "r"(a), "r"(cta)); return r;
}
__device__ __forceinline__ void mbar_arrive_remote(uint32_t ra) {
    asm volatile("mbarrier.arrive.shared::cluster.b64 _, [%0];" ::"r"(ra) : "memory");
}
__device__ __forceinline__ void bulk_load(uint32_t dst, const void* src, uint32_t bytes, uint32_t bar) {
    asm volatile("cp.async.bulk.shared::cluster.global.mbarrier::complete_tx::bytes [%0], [%1], %2, [%3];"
        ::"r"(dst), "l"(src), "r"(bytes), "r"(bar) : "memory");
}
__device__ __forceinline__ void bulk_load_hint(uint32_t dst, const void* src, uint32_t bytes, uint32_t bar, uint64_t pol) {
    asm volatile("cp.async.bulk.shared::cluster.global.mbarrier::complete_tx::bytes.L2::cache_hint [%0], [%1], %2, [%3], %4;"
        ::"r"(dst), "l"(src), "r"(bytes), "r"(bar), "l"(pol) : "memory");
}
__device__ __forceinline__ void bulk_load_mc(uint32_t dst, const void* src, uint32_t bytes, uint32_t bar, uint16_t mask) {
    asm volatile("cp.async.bulk.shared::cluster.global.mbarrier::complete_tx::bytes.multicast::cluster [%0], [%1], %2, [%3], %4;"
        ::"r"(dst), "l"(src), "r"(bytes), "r"(bar), "h"(mask) : "memory");
}
__device__ __forceinline__ void bulk_store(void* dst, uint32_t src, uint32_t bytes) {
    asm volatile("cp.async.bulk.global.shared::cta.bulk_group [%0], [%1], %2;" ::"l"(dst), "r"(src), "r"(bytes) : "memory");
}
__device__ __forceinline__ void tma_load_2d(uint32_t dst, const CUtensorMap* map, int c0, int c1, uint32_t bar) {
    asm volatile("cp.async.bulk.tensor.2d.shared::cluster.global.mbarrier::complete_tx::bytes [%0], [%1, {%3, %4}], [%2];"
        ::"r"(dst), "l"(map), "r"(bar), "r"(c0), "r"(c1) : "memory");
}
__device__ __forceinline__ void cluster_arrive() { asm volatile("barrier.cluster.arrive.relaxed.aligned;" ::: "memory"); }
__device__ __forceinline__ void cluster_arrive_release() { asm volatile("barrier.cluster.arrive.release.aligned;" ::: "memory"); }
__device__ __forceinline__ void cluster_wait() { asm volatile("barrier.cluster.wait.aligned;" ::: "memory"); }
__device__ __forceinline__ void wg_fence() { asm volatile("wgmma.fence.sync.aligned;" ::: "memory"); }
__device__ __forceinline__ void wg_commit() { asm volatile("wgmma.commit_group.sync.aligned;" ::: "memory"); }
template <int N> __device__ __forceinline__ void wg_wait() { asm volatile("wgmma.wait_group.sync.aligned %0;" ::"n"(N) : "memory"); }
__device__ __forceinline__ void bar_sync(int id, int n) { asm volatile("bar.sync %0, %1;" ::"r"(id), "r"(n) : "memory"); }
__device__ __forceinline__ void bar_arrive(int id, int n) { asm volatile("bar.arrive %0, %1;" ::"r"(id), "r"(n) : "memory"); }

__device__ __forceinline__ float ex2(float x) { float y; asm("ex2.approx.ftz.f32 %0, %1;" : "=f"(y) : "f"(x)); return y; }
__device__ __forceinline__ uint32_t pack_bf16(float lo, float hi) {
    uint32_t r; asm("cvt.rn.bf16x2.f32 %0, %1, %2;" : "=r"(r) : "f"(hi), "f"(lo)); return r;
}
__device__ __forceinline__ uint32_t bf2_sub(uint32_t a, uint32_t b) { uint32_t r; asm("sub.rn.bf16x2 %0, %1, %2;" : "=r"(r) : "r"(a), "r"(b)); return r; }
__device__ __forceinline__ uint32_t bf2_mul(uint32_t a, uint32_t b) { uint32_t r; asm("mul.rn.bf16x2 %0, %1, %2;" : "=r"(r) : "r"(a), "r"(b)); return r; }
__device__ __forceinline__ uint32_t bf2_fma(uint32_t a, uint32_t b, uint32_t c) { uint32_t r; asm("fma.rn.bf16x2 %0, %1, %2, %3;" : "=r"(r) : "r"(a), "r"(b), "r"(c)); return r; }

#define F8(a, i) "+f"(a[i]), "+f"(a[i + 1]), "+f"(a[i + 2]), "+f"(a[i + 3]), "+f"(a[i + 4]), "+f"(a[i + 5]), "+f"(a[i + 6]), "+f"(a[i + 7])
#define F64(a) F8(a, 0), F8(a, 8), F8(a, 16), F8(a, 24), F8(a, 32), F8(a, 40), F8(a, 48), F8(a, 56)

template <int TB>
__device__ __forceinline__ void wgmma_rs(float (&d)[64], uint32_t a0, uint32_t a1, uint32_t a2, uint32_t a3, uint64_t desc, int scale_d) {
    asm volatile(
        "{\n.reg .pred p;\nsetp.ne.b32 p, %69, 0;\n"
        "wgmma.mma_async.sync.aligned.m64n128k16.f32.bf16.bf16 "
        "{%0,%1,%2,%3,%4,%5,%6,%7,%8,%9,%10,%11,%12,%13,%14,%15,"
        "%16,%17,%18,%19,%20,%21,%22,%23,%24,%25,%26,%27,%28,%29,%30,%31,"
        "%32,%33,%34,%35,%36,%37,%38,%39,%40,%41,%42,%43,%44,%45,%46,%47,"
        "%48,%49,%50,%51,%52,%53,%54,%55,%56,%57,%58,%59,%60,%61,%62,%63},"
        "{%64,%65,%66,%67}, %68, p, 1, 1, %70;\n}\n"
        : F64(d)
        : "r"(a0), "r"(a1), "r"(a2), "r"(a3), "l"(desc), "r"(scale_d), "n"(TB));
}
__device__ __forceinline__ void fence_regs(float (&d)[64]) {
#pragma unroll
    for (int i = 0; i < 64; i++) asm volatile("" : "+f"(d[i])::"memory");
}
__device__ __forceinline__ void fence_regs(uint32_t (&d)[32]) {
#pragma unroll
    for (int i = 0; i < 32; i++) asm volatile("" : "+r"(d[i])::"memory");
}

struct DqItem { int kv, head, p, tok; };
__device__ __forceinline__ DqItem item_decode(int it, int h0, int h0inv) {
    DqItem d;
    const int su = it / ITEMS_PER_UNIT, part = it % ITEMS_PER_UNIT;
    if (su < UNITS_PER_HEAD * h0) { d.p = (su * h0inv) >> 16; d.head = su - d.p * h0; }
    else { const int x = su - UNITS_PER_HEAD * h0; d.head = h0 + x / UNITS_PER_HEAD; d.p = x % UNITS_PER_HEAD; }
    int blk;
    if (d.p == 0) { d.kv = 0; blk = 0; }
    else if (d.p == UNITS_PER_HEAD - 1) { d.kv = 1; blk = NBLK - 1; }
    else if (d.p & 1) { d.kv = 0; blk = (d.p + 1) >> 1; }
    else { d.kv = 1; blk = (d.p >> 1) - 1; }
    d.tok = blk * BN + part * 4;
    return d;
}
struct DqPtrs {
    const int* qk; const int* qv;
    const __nv_bfloat16 *ks, *kz, *vs, *vz;
};
__device__ __forceinline__ uint8_t* kv_tile(int kv, int head, int blk) {
    return reinterpret_cast<uint8_t*>(g_kv) + (size_t)((kv * HKV + head) * NBLK + blk) * TILE_BYTES;
}
__device__ __forceinline__ uint32_t codes_bf2(int a, int b) { return pack_bf16(__int2float_rn(a), __int2float_rn(b)); }
__device__ __forceinline__ void k_scale_split(uint32_t s, uint32_t& hi, uint32_t& lo) {
    const float f0 = __uint_as_float(s << 16) * SCALE_LOG2, f1 = __uint_as_float(s & 0xffff0000u) * SCALE_LOG2;
    hi = pack_bf16(f0, f1);
    lo = pack_bf16(f0 - __uint_as_float(hi << 16), f1 - __uint_as_float(hi & 0xffff0000u));
}
__device__ __forceinline__ uint32_t dq_k(int a, int b, uint32_t z, uint32_t hi, uint32_t lo) {
    const uint32_t t = bf2_sub(codes_bf2(a, b), z);
    return bf2_fma(t, hi, bf2_mul(t, lo));
}
__device__ __forceinline__ uint32_t dq_v(int a, int b, uint32_t z, uint32_t s) { return bf2_mul(bf2_sub(codes_bf2(a, b), z), s); }

__device__ __forceinline__ void ldg_stream2(int& a, int& b, const int* p, uint64_t pol) {
    asm volatile("ld.global.nc.L1::no_allocate.L2::cache_hint.v2.s32 {%0, %1}, [%2], %3;" : "=r"(a), "=r"(b) : "l"(p), "l"(pol));
}
__device__ __forceinline__ void ldg_stream4(int& a, int& b, int& c, int& d, const int* p, uint64_t pol) {
    asm volatile("ld.global.nc.L1::no_allocate.L2::cache_hint.v4.s32 {%0, %1, %2, %3}, [%4], %5;" : "=r"(a), "=r"(b), "=r"(c), "=r"(d) : "l"(p), "l"(pol));
}
__device__ __forceinline__ void dq_load(int (&v)[16], uint32_t (&zs)[4], const DqItem& d, int lane, const DqPtrs& g, uint64_t pol) {
    if (d.kv == 0) {
        const int* src = g.qk + (size_t)(d.head * SEQ + d.tok) * DH + 4 * lane;
#pragma unroll
        for (int r = 0; r < 4; r++) ldg_stream4(v[4 * r], v[4 * r + 1], v[4 * r + 2], v[4 * r + 3], src + r * DH, pol);
        const int so = (d.head * NGK + d.tok / GRP) * DH + 4 * lane;
        const uint2 zz = __ldg(reinterpret_cast<const uint2*>(g.kz + so)), ss = __ldg(reinterpret_cast<const uint2*>(g.ks + so));
        zs[0] = zz.x; zs[1] = zz.y; zs[2] = ss.x; zs[3] = ss.y;
    } else {
        const int tk = d.head * SEQ + d.tok + (lane >> 4);
        const int* src = g.qv + (size_t)tk * DH + 32 * ((lane & 15) >> 2) + 2 * (lane & 3);
        const unsigned short* z = reinterpret_cast<const unsigned short*>(g.vz) + tk;
        const unsigned short* sc = reinterpret_cast<const unsigned short*>(g.vs) + tk;
#pragma unroll
        for (int r = 0; r < 2; r++) {
#pragma unroll
            for (int c = 0; c < 4; c++) ldg_stream2(v[8 * r + 2 * c], v[8 * r + 2 * c + 1], src + 2 * r * DH + 8 * c, pol);
            zs[r] = __ldg(z + 2 * r); zs[2 + r] = __ldg(sc + 2 * r);
        }
    }
}
__device__ __forceinline__ void dq_convert_store(const int (&v)[16], const uint32_t (&zs)[4], const DqItem& d, int lane) {
    const int tr = d.tok % BN;
    uint8_t* tile = kv_tile(d.kv, d.head, d.tok / BN);
    if (d.kv == 0) {
        uint32_t h0, l0, h1, l1;
        k_scale_split(zs[2], h0, l0); k_scale_split(zs[3], h1, l1);
        uint8_t* dst = tile + (lane >> 4) * (TILE_BYTES / 2) + (lane & 1) * 8 + tr * 128;
        const int ch = (lane & 15) >> 1;
#pragma unroll
        for (int r = 0; r < 4; r++)
            *reinterpret_cast<uint2*>(dst + r * 128 + ((ch ^ ((tr + r) & 7)) << 4)) =
                make_uint2(dq_k(v[4 * r], v[4 * r + 1], zs[0], h0, l0), dq_k(v[4 * r + 2], v[4 * r + 3], zs[1], h1, l1));
    } else {
        const int i = (lane & 15) >> 2, ch = 4 * (i & 1) + (lane & 3), t0 = tr + (lane >> 4);
        uint8_t* dst = tile + (i >> 1) * (TILE_BYTES / 2) + t0 * 128;
#pragma unroll
        for (int r = 0; r < 2; r++) {
            const uint32_t z = zs[r] * 0x10001u, s = zs[2 + r] * 0x10001u;
            *reinterpret_cast<uint4*>(dst + 2 * r * 128 + ((ch ^ ((t0 + 2 * r) & 7)) << 4)) =
                make_uint4(dq_v(v[8 * r], v[8 * r + 1], z, s), dq_v(v[8 * r + 2], v[8 * r + 3], z, s),
                           dq_v(v[8 * r + 4], v[8 * r + 5], z, s), dq_v(v[8 * r + 6], v[8 * r + 7], z, s));
        }
    }
}
__device__ __forceinline__ void dq_signal(const DqItem& d, int lane) {
    asm volatile("fence.proxy.async.global;" ::: "memory");
    __syncwarp();
    if (lane == 0) asm volatile("red.release.gpu.global.add.u32 [%0], 1;" ::"l"(g_cnt + d.head * UNITS_PER_HEAD + d.p) : "memory");
}
__device__ __forceinline__ void dequant_loop(int it, int stride, int end, int h0, int h0inv, int lane, const DqPtrs& g, uint64_t pol) {
    if (it >= end) return;
    DqItem d = item_decode(it, h0, h0inv);
    int v[16]; uint32_t zs[4];
    dq_load(v, zs, d, lane, g, pol);
    while (true) {
        dq_convert_store(v, zs, d, lane);
        const DqItem dc = d;
        it += stride;
        const bool more = it < end;
        if (more) {
            d = item_decode(it, h0, h0inv);
            dq_load(v, zs, d, lane, g, pol);
        }
        dq_signal(dc, lane);
        if (!more) break;
    }
}
__device__ __forceinline__ void dq_bulk_zs(uint32_t (&zs)[16], uint32_t zi, int lane, const DqPtrs& g) {
    if (!(zi >> 31)) {
        const uint32_t so = zi + 4 * lane;
        const uint2 zz = __ldg(reinterpret_cast<const uint2*>(g.kz + so)), ss = __ldg(reinterpret_cast<const uint2*>(g.ks + so));
        zs[0] = zz.x; zs[1] = zz.y; zs[2] = ss.x; zs[3] = ss.y;
    } else {
        const uint4* z = reinterpret_cast<const uint4*>(g.vz + (zi & 0x7fffffffu));
        const uint4* s = reinterpret_cast<const uint4*>(g.vs + (zi & 0x7fffffffu));
        const uint4 z0 = __ldg(z), z1 = __ldg(z + 1), s0 = __ldg(s), s1 = __ldg(s + 1);
        zs[0] = z0.x; zs[1] = z0.y; zs[2] = z0.z; zs[3] = z0.w; zs[4] = z1.x; zs[5] = z1.y; zs[6] = z1.z; zs[7] = z1.w;
        zs[8] = s0.x; zs[9] = s0.y; zs[10] = s0.z; zs[11] = s0.w; zs[12] = s1.x; zs[13] = s1.y; zs[14] = s1.z; zs[15] = s1.w;
    }
}
__device__ __forceinline__ void dq_bulk_convert(const int (&v)[64], const uint32_t (&zs)[16], int kv, uint32_t dst, int lane) {
    if (kv == 0) {
        uint32_t h0, l0, h1, l1;
        k_scale_split(zs[2], h0, l0); k_scale_split(zs[3], h1, l1);
        const uint32_t a = dst + (lane >> 4) * 2048 + (lane & 1) * 8;
        const int ch = (lane & 15) >> 1;
#pragma unroll
        for (int r = 0; r < 16; r++)
            asm volatile("st.shared.v2.u32 [%0], {%1, %2};" ::"r"(a + r * 128 + ((ch ^ (r & 7)) << 4)),
                         "r"(dq_k(v[4 * r], v[4 * r + 1], zs[0], h0, l0)), "r"(dq_k(v[4 * r + 2], v[4 * r + 3], zs[1], h1, l1)) : "memory");
    } else {
        const int i = lane >> 3, c = (lane & 7) >> 1, ch = 4 * (i & 1) + 2 * (lane & 1);
        const uint32_t a = dst + (i >> 1) * 2048 + 4 * c;
#pragma unroll
        for (int r = 0; r < 16; r++) {
            const uint32_t sel = (r & 1) ? 0x3232u : 0x1010u;
            const uint32_t z = __byte_perm(zs[r >> 1], 0, sel), s = __byte_perm(zs[8 + (r >> 1)], 0, sel);
            asm volatile("st.shared.u32 [%0], %1;" ::"r"(a + r * 128 + ((ch ^ (r & 7)) << 4)), "r"(dq_v(v[4 * r], v[4 * r + 1], z, s)) : "memory");
            asm volatile("st.shared.u32 [%0], %1;" ::"r"(a + r * 128 + (((ch + 1) ^ (r & 7)) << 4)), "r"(dq_v(v[4 * r + 2], v[4 * r + 3], z, s)) : "memory");
        }
    }
}

template <int V> struct IC { static constexpr int value = V; };
struct Ring {
    uint32_t slot, phase, desc;
    __device__ __forceinline__ void advance() {
        slot += 1; desc += STAGE_BYTES >> 4;
        if (slot == NST) { slot = 0; desc -= NST * (STAGE_BYTES >> 4); phase ^= 1; }
    }
};

__device__ __forceinline__ void load_q(uint32_t (&qf)[32], uint32_t qrow, uint32_t qsw) {
#pragma unroll
    for (int kk = 0; kk < 8; kk++)
        asm volatile("ldmatrix.sync.aligned.m8n8.x4.shared.b16 {%0, %1, %2, %3}, [%4];"
                     : "=r"(qf[4 * kk]), "=r"(qf[4 * kk + 1]), "=r"(qf[4 * kk + 2]), "=r"(qf[4 * kk + 3])
                     : "r"(qrow + (kk >> 2) * (QBUF_BYTES / 2) + (qsw ^ ((kk & 3) << 5))) : "memory");
}
__device__ __forceinline__ uint32_t tile_desc(uint32_t addr) { return (addr & 0x3FFFFu) >> 4; }
__device__ __forceinline__ uint32_t k_desc(uint32_t d) { return d | (1u << 16); }
__device__ __forceinline__ uint32_t v_desc(uint32_t d) { return d | (1024u << 16); }
__device__ __forceinline__ void issue_qk(float (&S)[64], const uint32_t (&qf)[32], uint32_t lo) {
    const uint64_t hi = (uint64_t)(64u | (1u << 30)) << 32;
#pragma unroll
    for (int kk = 0; kk < 8; kk++)
        wgmma_rs<0>(S, qf[4 * kk], qf[4 * kk + 1], qf[4 * kk + 2], qf[4 * kk + 3],
                    hi | (uint64_t)(lo + (kk >> 2) * 1024 + (kk & 3) * 2), kk != 0);
}
__device__ __forceinline__ void issue_pv(float (&O)[64], const uint32_t (&P)[32], uint32_t lo, int acc) {
    const uint64_t hi = (uint64_t)(64u | (1u << 30)) << 32;
#pragma unroll
    for (int kk = 0; kk < 8; kk++)
        wgmma_rs<1>(O, P[4 * kk], P[4 * kk + 1], P[4 * kk + 2], P[4 * kk + 3], hi | (uint64_t)(lo + kk * 128), kk != 0 ? 1 : acc);
}
template <int J0, int J1>
__device__ __forceinline__ void exp_part(float (&S)[64], float (&acc)[4]) {
#pragma unroll
    for (int j = J0; j < J1; j++) {
        S[4 * j + 0] = ex2(S[4 * j + 0]);
        S[4 * j + 1] = ex2(S[4 * j + 1]);
        S[4 * j + 2] = ex2(S[4 * j + 2]);
        S[4 * j + 3] = ex2(S[4 * j + 3]);
        if (j == 0) { acc[0] = S[0]; acc[1] = S[1]; acc[2] = S[2]; acc[3] = S[3]; }
        else { acc[0] += S[4 * j + 0]; acc[1] += S[4 * j + 1]; acc[2] += S[4 * j + 2]; acc[3] += S[4 * j + 3]; }
    }
}
__device__ __forceinline__ void cvt_p(const float (&S)[64], uint32_t (&P)[32]) {
#pragma unroll
    for (int j = 0; j < 16; j++) {
        P[2 * j] = pack_bf16(S[4 * j], S[4 * j + 1]);
        P[2 * j + 1] = pack_bf16(S[4 * j + 2], S[4 * j + 3]);
    }
}
__device__ __forceinline__ bool finish_l(float l0, float l1, float& i0, float& i1) {
    l0 += __shfl_xor_sync(0xffffffffu, l0, 1); l1 += __shfl_xor_sync(0xffffffffu, l1, 1);
    l0 += __shfl_xor_sync(0xffffffffu, l0, 2); l1 += __shfl_xor_sync(0xffffffffu, l1, 2);
    asm("rcp.approx.ftz.f32 %0, %1;" : "=f"(i0) : "f"(l0));
    asm("rcp.approx.ftz.f32 %0, %1;" : "=f"(i1) : "f"(l1));
    return l0 >= L_MIN && l0 <= L_MAX && l1 >= L_MIN && l1 <= L_MAX;
}
__device__ __forceinline__ bool store_o(const float (&O)[64], float i0, float i1, __nv_bfloat16* __restrict__ orow) {
    float c0 = 0.f, c1 = 0.f, c2 = 0.f, c3 = 0.f;
#pragma unroll
    for (int i = 0; i < 4; i++) {
        uint4 a, b;
        a.x = pack_bf16(O[16 * i + 0] * i0, O[16 * i + 1] * i0);
        a.y = pack_bf16(O[16 * i + 4] * i0, O[16 * i + 5] * i0);
        a.z = pack_bf16(O[16 * i + 8] * i0, O[16 * i + 9] * i0);
        a.w = pack_bf16(O[16 * i + 12] * i0, O[16 * i + 13] * i0);
        b.x = pack_bf16(O[16 * i + 2] * i1, O[16 * i + 3] * i1);
        b.y = pack_bf16(O[16 * i + 6] * i1, O[16 * i + 7] * i1);
        b.z = pack_bf16(O[16 * i + 10] * i1, O[16 * i + 11] * i1);
        b.w = pack_bf16(O[16 * i + 14] * i1, O[16 * i + 15] * i1);
        *reinterpret_cast<uint4*>(orow + 32 * i) = a;
        *reinterpret_cast<uint4*>(orow + 8 * DH + 32 * i) = b;
#pragma unroll
        for (int e = 0; e < 16; e += 4) {
            c0 = fmaf(O[16 * i + e], 0.f, c0); c1 = fmaf(O[16 * i + e + 1], 0.f, c1);
            c2 = fmaf(O[16 * i + e + 2], 0.f, c2); c3 = fmaf(O[16 * i + e + 3], 0.f, c3);
        }
    }
    return (c0 + c1) + (c2 + c3) == 0.f;
}

struct Sched {
    int rem;
    int nlight;
    int bulk;
    int h0, h0inv;
    int nhelp;
    int nfirst;
};

__global__ void __cluster_dims__(2, 1, 1) __launch_bounds__(384, 1)
attn_kernel(const __grid_constant__ CUtensorMap qmap, const int* __restrict__ qk, const int* __restrict__ qv,
            const __nv_bfloat16* __restrict__ ks, const __nv_bfloat16* __restrict__ kz,
            const __nv_bfloat16* __restrict__ vs, const __nv_bfloat16* __restrict__ vz,
            __nv_bfloat16* __restrict__ out, const Sched sc) {
    extern __shared__ __align__(1024) uint8_t smem_raw[];
    const uint32_t sb = smem_u32(smem_raw);
    const uint32_t qbuf = sb + NS * TILE_BYTES;
    const uint32_t bar_full = qbuf + QBUF_BYTES, bar_empty = bar_full + 8 * NS;
    const uint32_t bar_qfull = bar_empty + 8 * NS, bar_qempty = bar_qfull + 8, pin_addr = bar_qempty + 8;
    const uint32_t bar_dfull = pin_addr + 8;
    const uint32_t bar_bempty = bar_dfull + 8;
    const uint32_t bar_rfull = bar_bempty + 8 * NIN, bar_rempty = bar_rfull + 16;
    const uint32_t bar_bfull = bar_rempty + 16, bar_bdone = bar_bfull + 8 * MAX_CHUNKS_PER_CTA;
    const uint32_t chunk_tab = bar_full + 1280;
    volatile uint8_t* redo = smem_raw + NS * TILE_BYTES + QBUF_BYTES + 1024;
    const int wg = __shfl_sync(0xffffffffu, threadIdx.x >> 7, 0);
    const int warp = __shfl_sync(0xffffffffu, (threadIdx.x >> 5) & 3, 0);
    const int lane = threadIdx.x & 31;
    uint32_t rank; asm("mov.u32 %0, %%cluster_ctarank;" : "=r"(rank));
    const int cluster_id = blockIdx.x >> 1, nclusters = gridDim.x >> 1;

    const bool light = sc.bulk && cluster_id >= sc.rem;
    const int h0 = sc.h0, h0inv = sc.h0inv;
    const int chunk0 = sc.nfirst / ITEMS_PER_CHUNK + (int)blockIdx.x - 2 * sc.rem, chunk_stride = 2 * sc.nlight;
    const int nchunks = light ? (NCHUNKS - chunk0 + chunk_stride - 1) / chunk_stride : 0;
    const DqPtrs dq{qk, qv, ks, kz, vs, vz};
    uint64_t pol;
    asm volatile("createpolicy.fractional.L2::evict_first.b64 %0, 1.0;" : "=l"(pol));
    const int gwarp = wg * 4 + warp;

    if (gwarp == 0) {
        if (sb & 1023u) __trap();
        if (lane < NST) { mbar_init(bar_full + 8 * lane, 1); mbar_init(bar_empty + 8 * lane, 4); }
        if (lane == 8) { mbar_init(bar_qfull, 1); mbar_init(bar_qempty, 8); mbar_init(bar_dfull, 1); }
        if (lane == 9 || lane == 10) { mbar_init(bar_rfull + 8 * (lane - 9), 1); mbar_init(bar_rempty + 8 * (lane - 9), 2); }
        if (light) {
            if (lane >= 16 && lane < 16 + NIN) mbar_init(bar_bempty + 8 * (lane - 16), 4);
            for (int s = lane; s < nchunks; s += 32) {
                mbar_init(bar_bfull + 8 * s, 1); mbar_init(bar_bdone + 8 * s, 4);
                const DqItem d = item_decode((chunk0 + s * chunk_stride) * ITEMS_PER_CHUNK, h0, h0inv);
                const uint32_t w0 = (uint32_t)(kv_tile(d.kv, d.head, d.tok / BN) - reinterpret_cast<uint8_t*>(g_kv)) + (d.tok % BN) * 128;
                const uint32_t w1 = d.kv ? (0x80000000u | (uint32_t)(d.head * SEQ + d.tok)) : (uint32_t)((d.head * NGK + d.tok / GRP) * DH);
                asm volatile("st.shared.v4.u32 [%0], {%1, %2, %3, %4};" ::"r"(chunk_tab + 16 * s), "r"(w0), "r"(w1),
                             "r"((uint32_t)((d.head * SEQ + d.tok) * DH)), "r"((uint32_t)(d.head * UNITS_PER_HEAD + d.p)) : "memory");
            }
        }
        asm volatile("fence.mbarrier_init.release.cluster;\nfence.acq_rel.cta;" ::: "memory");
        __syncwarp();
        if (lane == 0 && (light || !Q_AFTER)) {
            mbar_expect_tx(bar_qfull, QBUF_BYTES);
            tma_load_2d(qbuf, &qmap, 0, cluster_id * 256 + rank * 128, bar_qfull);
            tma_load_2d(qbuf + QBUF_BYTES / 2, &qmap, 64, cluster_id * 256 + rank * 128, bar_qfull);
        }
        __syncwarp();
        cluster_arrive();
        if (light) {
            if (lane == 0) {
                const long long t0 = clock64();
                while (clock64() - t0 < LOADER_DELAY) {}
                for (int k = 0; k < nchunks; k++) {
                    const int slot = k % NIN;
                    const uint4 e = ld_shared_v4(chunk_tab + 16 * k);
                    mbar_wait_sleep(bar_bempty + 8 * slot, ((k / NIN) & 1) ^ 1);
                    mbar_expect_tx(bar_bfull + 8 * k, TILE_BYTES);
                    bulk_load_hint(sb + slot * TILE_BYTES, ((e.y >> 31) ? qv : qk) + e.z, TILE_BYTES, bar_bfull + 8 * k, pol);
                }
            }
            __syncwarp();
        }
        cluster_wait();
        if (!light && lane == 0) {
            mbar_expect_tx(bar_dfull, STAGE_BYTES);
            bulk_load_mc(sb + (NST - 1) * STAGE_BYTES + rank * TILE_BYTES, qk + (size_t)((cluster_id / TILES_PER_HEAD) * SEQ + rank * 64) * DH,
                         TILE_BYTES, bar_dfull, (uint16_t)3);
            if (Q_AFTER) {
                mbar_expect_tx(bar_qfull, QBUF_BYTES);
                tma_load_2d(qbuf, &qmap, 0, cluster_id * 256 + rank * 128, bar_qfull);
                tma_load_2d(qbuf + QBUF_BYTES / 2, &qmap, 64, cluster_id * 256 + rank * 128, bar_qfull);
            }
        }
        __syncwarp();
    } else {
        cluster_arrive();
        if (light || wg != 0) cluster_wait();
        if (light && gwarp == 1) {
            if (lane == 0) {
                for (int sig = 0; sig < nchunks;) {
                    mbar_wait_sleep(bar_bdone + 8 * sig, 0);
                    int m = 1;
                    while (m < 4 && sig + m < nchunks && mbar_test(bar_bdone + 8 * (sig + m), 0)) m++;
                    asm volatile("fence.acq_rel.gpu;" ::: "memory");
                    for (int i = 0; i < m; i++) {
                        const uint4 e = ld_shared_v4(chunk_tab + 16 * (sig + i));
                        asm volatile("red.relaxed.gpu.global.add.u32 [%0], %1;" ::"l"(g_cnt + e.w), "r"(ITEMS_PER_CHUNK) : "memory");
                    }
                    sig += m;
                }
            }
            __syncwarp();
        } else if (light) {
            const uint32_t obuf = sb + NIN * TILE_BYTES + (gwarp - 2) * 4096;
            const int nq = 4 * nchunks;
            int j = gwarp - 2, kprev = -1;
            uint32_t ooff = 0, zi = 0, zs[16];
            auto prepare = [&](int jj, uint32_t& ooff_, uint32_t& zi_, uint32_t (&zs_)[16]) {
                const uint4 e = ld_shared_v4(chunk_tab + 16 * (jj >> 2));
                ooff_ = e.x + (jj & 3) * 2048;
                zi_ = e.y + ((e.y >> 31) ? (jj & 3) * 16 : 0);
                dq_bulk_zs(zs_, zi_, lane, dq);
            };
            if (j < nq) prepare(j, ooff, zi, zs);
            while (j < nq) {
                const int k = j >> 2, slot = k % NIN;
                mbar_wait(bar_bfull + 8 * k, 0);
                int v[64];
                const uint32_t src = sb + slot * TILE_BYTES + (j & 3) * 8192 + lane * 16;
#pragma unroll
                for (int r = 0; r < 16; r++)
                    asm volatile("ld.shared.v4.s32 {%0, %1, %2, %3}, [%4];" : "=r"(v[4 * r]), "=r"(v[4 * r + 1]), "=r"(v[4 * r + 2]), "=r"(v[4 * r + 3])
                                 : "r"(src + r * 512) : "memory");
                uint32_t ooffn = 0, zin = 0, zsn[16];
                if (j + 10 < nq) prepare(j + 10, ooffn, zin, zsn);
                __syncwarp();
                if (lane == 0) {
                    mbar_arrive(bar_bempty + 8 * slot);
                    if (kprev >= 0) {
                        asm volatile("cp.async.bulk.wait_group 0;" ::: "memory");
                        mbar_arrive(bar_bdone + 8 * kprev);
                    }
                }
                __syncwarp();
                dq_bulk_convert(v, zs, zi >> 31, obuf, lane);
                asm volatile("fence.proxy.async.shared::cta;" ::: "memory");
                __syncwarp();
                if (lane == 0) {
                    uint8_t* o = reinterpret_cast<uint8_t*>(g_kv) + ooff;
                    bulk_store(o, obuf, 2048);
                    bulk_store(o + TILE_BYTES / 2, obuf + 2048, 2048);
                    asm volatile("cp.async.bulk.commit_group;" ::: "memory");
                }
                kprev = k;
                j += 10;
                ooff = ooffn; zi = zin;
#pragma unroll
                for (int i = 0; i < 16; i++) zs[i] = zsn[i];
            }
            if (kprev >= 0 && lane == 0) {
                asm volatile("cp.async.bulk.wait_group 0;" ::: "memory");
                mbar_arrive(bar_bdone + 8 * kprev);
            }
            __syncwarp();
        }
    }
    if (light) { cluster_arrive_release(); cluster_wait(); }

    if (wg == 0) {
        asm volatile("setmaxnreg.dec.sync.aligned.u32 56;");
        if (warp == 0) {
            uint32_t qphase = 0;
            auto load_qtile = [&](int t) {
                if (lane == 0) {
                    mbar_wait(bar_qempty, qphase);
                    mbar_expect_tx(bar_qfull, QBUF_BYTES);
                    tma_load_2d(qbuf, &qmap, 0, t * 256 + rank * 128, bar_qfull);
                    tma_load_2d(qbuf + QBUF_BYTES / 2, &qmap, 64, t * 256 + rank * 128, bar_qfull);
                }
                __syncwarp();
                qphase ^= 1;
            };
            Ring r{0, 1, 0};
            int vhead = -1;
            uint32_t vmask = 0;
            auto await_unit = [&](int kv, int head, int blk) {
                const int p = kv == 0 ? (blk == 0 ? 0 : 2 * blk - 1) : (blk == NBLK - 1 ? UNITS_PER_HEAD - 1 : 2 * blk + 2);
                if (head != vhead) { vhead = head; vmask = 0; }
                if (!((vmask >> p) & 1)) {
                    uint32_t n = 0;
                    while (true) {
                        unsigned int c;
                        asm volatile("ld.acquire.gpu.global.u32 %0, [%1];" : "=r"(c) : "l"(g_cnt + head * UNITS_PER_HEAD + lane) : "memory");
                        vmask = __ballot_sync(0xffffffffu, c == ITEMS_PER_UNIT);
                        if ((vmask >> p) & 1) break;
                        if (++n > (1u << 22)) __trap();
                    }
                    asm volatile("fence.proxy.async.global;" ::: "memory");
                }
            };
            auto load = [&](int khead, int kblk, int vh, int vblk) {
                if (vh >= 0) await_unit(1, vh, vblk);
                if (khead >= 0) await_unit(0, khead, kblk);
                if (lane == 0) {
                    const uint32_t full = bar_full + 8 * r.slot, dst = sb + r.slot * STAGE_BYTES + rank * (TILE_BYTES / 2);
                    mbar_wait_sleep(bar_empty + 8 * r.slot, r.phase ^ (uint32_t)(!light && r.slot == NST - 1));
                    mbar_expect_tx(full, (khead >= 0 ? TILE_BYTES : 0) + (vh >= 0 ? TILE_BYTES : 0));
                    if (khead >= 0) bulk_load_mc(dst, kv_tile(0, khead, kblk) + rank * (TILE_BYTES / 2), TILE_BYTES / 2, full, (uint16_t)3);
                    if (vh >= 0) bulk_load_mc(dst + TILE_BYTES, kv_tile(1, vh, vblk) + rank * (TILE_BYTES / 2), TILE_BYTES / 2, full, (uint16_t)3);
                }
                __syncwarp();
                r.advance();
            };
            if (light) load(cluster_id / TILES_PER_HEAD, 0, -1, 0);
            else {
                if (lane == 0) mbar_arrive(bar_full);
                __syncwarp();
                r.advance();
            }
            for (int t = cluster_id; t < NTILES; t += nclusters) {
                const int head = t / TILES_PER_HEAD;
                const int tn = t + nclusters;
                for (int j = 0; j < NBLK; j++) {
                    if (j == 4 && tn < NTILES) load_qtile(tn);
                    if (j < NBLK - 1) load(head, j + 1, head, j);
                    else load(tn < NTILES ? tn / TILES_PER_HEAD : -1, 0, head, j);
                }
            }
            if (lane == 0) {
                const unsigned int prev = atomicAdd(&g_done, 1u);
                if (prev == gridDim.x - 1) {
                    for (int i = 0; i < HKV * UNITS_PER_HEAD; i++) g_cnt[i] = 0;
                    g_done = 0;
                }
            }
            __syncwarp();
            bar_sync(3, 288);
            uint32_t n = 0;
            for (int t = cluster_id, k = 0; t < NTILES; t += nclusters, k++) {
                if (!redo[k]) continue;
                load_qtile(t);
                if (lane == 0) {
                    for (int j = 0; j < 2 * NBLK; j++, n++) {
                        const uint32_t s = n & 1;
                        mbar_wait(bar_rempty + 8 * s, ((n >> 1) & 1) ^ 1);
                        mbar_expect_tx(bar_rfull + 8 * s, TILE_BYTES);
                        bulk_load(sb + s * TILE_BYTES, kv_tile(j & 1, t / TILES_PER_HEAD, j >> 1), TILE_BYTES, bar_rfull + 8 * s);
                    }
                }
                __syncwarp();
            }
        } else {
            if (!light) {
                dequant_loop(blockIdx.x * 3 + (warp - 1), sc.nhelp, sc.nfirst, h0, h0inv, lane, dq, pol);
                cluster_wait();
            }
        }
        cluster_arrive(); cluster_wait();
    } else {
        asm volatile("setmaxnreg.inc.sync.aligned.u32 224;");
        const int w = wg - 1;
        const int my_bar = 1 + w, other_bar = 2 - w;
        const int row_in_tile = rank * 128 + w * 64 + warp * 16 + (lane >> 2);
        const int coff = (lane & 3) * 8;
        const uint32_t qrow = qbuf + (w * 64 + warp * 16 + (lane & 15)) * 128;
        const uint32_t qsw = ((lane >> 4) ^ (lane & 7)) << 4;
        const uint32_t rem_empty = mapa(bar_empty, warp & 1);
        const bool releaser = lane == 0 && warp < 2;
        uint32_t qf[32], P[32];
        float S[64], O[64];
        float l0 = 0.f, l1 = 0.f, lo0 = 1.f, lo1 = 1.f;
        uint32_t qphase = 0;
        Ring r{0, 0, tile_desc(sb)};
        auto release = [&]() {
            if (releaser) mbar_arrive_remote(rem_empty + 8 * r.slot);
            r.advance();
        };
        auto reload_q = [&]() {
            mbar_wait(bar_qfull, qphase);
            qphase ^= 1;
            load_q(qf, qrow, qsw);
            __syncwarp();
            if (lane == 0) mbar_arrive(bar_qempty);
        };
        auto pin = [&](float x) {
            asm volatile("{\n.reg .pred p;\nsetp.eq.f32 p, %0, 0fBF800000;\n@p st.shared.f32 [%1], %0;\n}\n" ::"f"(x), "r"(pin_addr) : "memory");
        };
        int t = cluster_id, tk = 0;
#pragma unroll
        for (int i = 0; i < 64; i++) { S[i] = 0.f; O[i] = 0.f; }
        if (gwarp == 4) { reinterpret_cast<volatile uint32_t*>(redo)[lane] = 0; reinterpret_cast<volatile uint32_t*>(redo)[lane + 32] = 0; }
        if (w == 1) bar_arrive(1, 256);
        if (!light) {
            const int cw = w * 4 + warp;
            const int so = (cluster_id / TILES_PER_HEAD) * NGK * DH + 4 * lane;
            const uint2 zz = __ldg(reinterpret_cast<const uint2*>(kz + so)), ss = __ldg(reinterpret_cast<const uint2*>(ks + so));
            uint32_t h0_, l0_, h1_, l1_;
            k_scale_split(ss.x, h0_, l0_); k_scale_split(ss.y, h1_, l1_);
            mbar_wait(bar_dfull, 0);
            const uint32_t src = sb + (NST - 1) * STAGE_BYTES + cw * 8192 + lane * 16;
            const uint32_t dst = sb + (lane >> 4) * (TILE_BYTES / 2) + cw * 2048 + (lane & 1) * 8;
            const int ch = (lane & 15) >> 1;
#pragma unroll
            for (int i = 0; i < 16; i++) {
                int a, b, c, d;
                asm volatile("ld.shared.v4.s32 {%0, %1, %2, %3}, [%4];" : "=r"(a), "=r"(b), "=r"(c), "=r"(d) : "r"(src + i * 512) : "memory");
                asm volatile("st.shared.v2.u32 [%0], {%1, %2};" ::"r"(dst + i * 128 + ((ch ^ (i & 7)) << 4)),
                             "r"(dq_k(a, b, zz.x, h0_, l0_)), "r"(dq_k(c, d, zz.y, h1_, l1_)) : "memory");
            }
            asm volatile("fence.proxy.async.shared::cta;" ::: "memory");
            bar_sync(4, 256);
            if (releaser) mbar_arrive_remote(rem_empty + 8 * (NST - 1));
        }
        reload_q();
        {
            if (light) mbar_wait(bar_full, 0);
            bar_sync(my_bar, 256);
            wg_fence();
            issue_qk(S, qf, k_desc(r.desc));
            wg_commit();
            bar_arrive(other_bar, 256);
            wg_wait<0>();
            fence_regs(S);
            release();
            float acc[4];
            exp_part<0, 16>(S, acc);
            l0 = acc[0] + acc[1]; l1 = acc[2] + acc[3];
            cvt_p(S, P);
        }
        uint32_t ready = 0;
        auto step = [&](auto first, bool store_prev, __nv_bfloat16* orow, bool swap_l, bool new_q) {
            constexpr bool FIRST = decltype(first)::value;
            if (!ready) mbar_wait(bar_full + 8 * r.slot, r.phase);
            bar_sync(my_bar, 256);
            wg_fence();
            issue_qk(S, qf, k_desc(r.desc));
            wg_commit();
            if (FIRST) {
                if (store_prev) {
                    float i0, i1;
                    const bool ok = finish_l(lo0, lo1, i0, i1);
                    if (!store_o(O, i0, i1, orow) || !ok) redo[tk - 1] = 1;
                }
                fence_regs(O);
                wg_fence();
            }
            issue_pv(O, P, v_desc(r.desc + (TILE_BYTES >> 4)), !FIRST);
            wg_commit();
            bar_arrive(other_bar, 256);
            wg_wait<1>();
            fence_regs(S);
            if (!FIRST && new_q) { fence_regs(qf); reload_q(); }
            float acc[4];
            exp_part<0, PIN_J>(S, acc);
            pin((acc[0] + acc[1]) + (acc[2] + acc[3]));
            wg_wait<0>();
            fence_regs(O);
            fence_regs(P);
            release();
            ready = mbar_test(bar_full + 8 * r.slot, r.phase);
            exp_part<PIN_J, 16>(S, acc);
            cvt_p(S, P);
            if (!FIRST && swap_l) { lo0 = l0; lo1 = l1; l0 = 0.f; l1 = 0.f; }
            l0 += acc[0] + acc[1]; l1 += acc[2] + acc[3];
        };
        __nv_bfloat16* oprev = out;
        while (true) {
            const int tn = t + nclusters;
            const bool has_next = tn < NTILES;
            step(IC<1>{}, tk > 0, oprev, false, false);
            const int jend = has_next ? NBLK : NBLK - 1;
#pragma unroll 1
            for (int j = 1; j < jend; j++) step(IC<0>{}, false, nullptr, j == NBLK - 1, has_next && j == NBLK - 2);
            oprev = out + (size_t)(t * 256 + row_in_tile) * DH + coff;
            if (has_next) {
                t = tn; tk++;
            } else {
                mbar_wait(bar_full + 8 * r.slot, r.phase);
                bar_sync(my_bar, 256);
                wg_fence();
                issue_pv(O, P, v_desc(r.desc + (TILE_BYTES >> 4)), 1);
                wg_commit();
                if (w == 0) bar_arrive(other_bar, 256);
                wg_wait<0>();
                fence_regs(O);
                float i0, i1;
                const bool ok = finish_l(l0, l1, i0, i1);
                if (!store_o(O, i0, i1, oprev) || !ok) redo[tk] = 1;
                break;
            }
        }
        bar_sync(3, 288);
        uint32_t n = 0;
        for (int tt = cluster_id, k = 0; tt < NTILES; tt += nclusters, k++) {
            if (!redo[k]) continue;
            mbar_wait(bar_qfull, qphase);
            qphase ^= 1;
            float m0 = -INFINITY, m1 = -INFINITY;
            l0 = 0.f; l1 = 0.f;
#pragma unroll 1
            for (int j = 0; j < NBLK; j++) {
                load_q(qf, qrow, qsw);
                mbar_wait(bar_rfull + 8 * (n & 1), (n >> 1) & 1);
                wg_fence();
                issue_qk(S, qf, k_desc(tile_desc(sb + (n & 1) * TILE_BYTES)));
                wg_commit();
                wg_wait<0>();
                fence_regs(S);
                if (warp == 0 && lane == 0) mbar_arrive(bar_rempty + 8 * (n & 1));
                n++;
                float a0 = m0, a1 = m1;
#pragma unroll
                for (int i = 0; i < 16; i++) {
                    a0 = fmaxf(a0, fmaxf(S[4 * i], S[4 * i + 1]));
                    a1 = fmaxf(a1, fmaxf(S[4 * i + 2], S[4 * i + 3]));
                }
                a0 = fmaxf(a0, __shfl_xor_sync(0xffffffffu, a0, 1)); a1 = fmaxf(a1, __shfl_xor_sync(0xffffffffu, a1, 1));
                a0 = fmaxf(a0, __shfl_xor_sync(0xffffffffu, a0, 2)); a1 = fmaxf(a1, __shfl_xor_sync(0xffffffffu, a1, 2));
                const float al0 = ex2(m0 - a0), al1 = ex2(m1 - a1);
                m0 = a0; m1 = a1;
#pragma unroll
                for (int i = 0; i < 16; i++) {
                    S[4 * i] -= a0; S[4 * i + 1] -= a0; S[4 * i + 2] -= a1; S[4 * i + 3] -= a1;
                    O[4 * i] *= al0; O[4 * i + 1] *= al0; O[4 * i + 2] *= al1; O[4 * i + 3] *= al1;
                }
                float acc[4];
                exp_part<0, 16>(S, acc);
                l0 = l0 * al0 + (acc[0] + acc[1]); l1 = l1 * al1 + (acc[2] + acc[3]);
                cvt_p(S, P);
                mbar_wait(bar_rfull + 8 * (n & 1), (n >> 1) & 1);
                wg_fence();
                issue_pv(O, P, v_desc(tile_desc(sb + (n & 1) * TILE_BYTES)), j != 0);
                wg_commit();
                wg_wait<0>();
                fence_regs(O);
                if (warp == 0 && lane == 0) mbar_arrive(bar_rempty + 8 * (n & 1));
                n++;
            }
            __syncwarp();
            if (lane == 0) mbar_arrive(bar_qempty);
            {
                float i0, i1;
                finish_l(l0, l1, i0, i1);
                store_o(O, i0, i1, out + (size_t)(tt * 256 + row_in_tile) * DH + coff);
            }
        }
        cluster_arrive(); cluster_wait();
    }
}

}

extern "C" void kernel_launch(void* const* d_in, const int* in_sizes, int n_in, void* d_out, int out_size) {
    const __nv_bfloat16* q = (const __nv_bfloat16*)d_in[0];
    const int* qk = (const int*)d_in[1];
    const int* qv = (const int*)d_in[2];
    const __nv_bfloat16* ks = (const __nv_bfloat16*)d_in[3];
    const __nv_bfloat16* kz = (const __nv_bfloat16*)d_in[4];
    const __nv_bfloat16* vs = (const __nv_bfloat16*)d_in[5];
    const __nv_bfloat16* vz = (const __nv_bfloat16*)d_in[6];
    typedef CUresult (*EncodeFn)(CUtensorMap*, CUtensorMapDataType, cuuint32_t, void*, const cuuint64_t*, const cuuint64_t*,
                                 const cuuint32_t*, const cuuint32_t*, CUtensorMapInterleave, CUtensorMapSwizzle,
                                 CUtensorMapL2promotion, CUtensorMapFloatOOBfill);
    static EncodeFn encode = nullptr;
    static int grid = 0;
    static Sched sc;
    if (grid == 0) {
        void* fn = nullptr;
        cudaDriverEntryPointQueryResult qr;
        cudaGetDriverEntryPoint("cuTensorMapEncodeTiled", &fn, cudaEnableDefault, &qr);
        encode = (EncodeFn)fn;
        cudaFuncSetAttribute(attn_kernel, cudaFuncAttributeMaxDynamicSharedMemorySize, SMEM_BYTES);
        cudaLaunchConfig_t cfg = {};
        cfg.gridDim = dim3(2, 1, 1); cfg.blockDim = dim3(384, 1, 1); cfg.dynamicSmemBytes = SMEM_BYTES;
        cudaLaunchAttribute at[1];
        at[0].id = cudaLaunchAttributeClusterDimension;
        at[0].val.clusterDim.x = 2; at[0].val.clusterDim.y = 1; at[0].val.clusterDim.z = 1;
        cfg.attrs = at; cfg.numAttrs = 1;
        int nc = 0;
        if (cudaOccupancyMaxActiveClusters(&nc, attn_kernel, &cfg) != cudaSuccess || nc <= 0) { nc = 1; (void)cudaGetLastError(); }
        if (nc > NTILES) nc = NTILES;
        if (FORCE_CLUSTERS) nc = FORCE_CLUSTERS;
        sc.rem = NTILES % nc;
        sc.nlight = sc.rem ? nc - sc.rem : 0;
        sc.bulk = sc.nlight >= MIN_LIGHT;
        const int lead = sc.bulk ? sc.rem : nc;
        sc.h0 = (lead + TILES_PER_HEAD - 1) / TILES_PER_HEAD;
        if (sc.h0 > HKV) sc.h0 = HKV;
        sc.h0inv = (65536 + sc.h0 - 1) / sc.h0;
        sc.nhelp = 2 * lead * 3;
        sc.nfirst = NITEMS;
        if (sc.bulk && ((sc.nhelp * NFIRST) & ~(ITEMS_PER_CHUNK - 1)) < NITEMS) sc.nfirst = (sc.nhelp * NFIRST) & ~(ITEMS_PER_CHUNK - 1);
        grid = nc * 2;
    }
    CUtensorMap qmap;
    const cuuint64_t dims[2] = {(cuuint64_t)DH, (cuuint64_t)HQ * SEQ};
    const cuuint64_t strides[1] = {(cuuint64_t)DH * 2};
    const cuuint32_t box[2] = {64, 128};
    const cuuint32_t estr[2] = {1, 1};
    encode(&qmap, CU_TENSOR_MAP_DATA_TYPE_BFLOAT16, 2, (void*)q, dims, strides, box, estr, CU_TENSOR_MAP_INTERLEAVE_NONE,
           CU_TENSOR_MAP_SWIZZLE_128B, CU_TENSOR_MAP_L2_PROMOTION_L2_128B, CU_TENSOR_MAP_FLOAT_OOB_FILL_NONE);
    attn_kernel<<<grid, 384, SMEM_BYTES>>>(qmap, qk, qv, ks, kz, vs, vz, (__nv_bfloat16*)d_out, sc);
}
```

```cpp
#include <cuda_runtime.h>
#include <cuda_bf16.h>
#include <cuda.h>
#include <stdint.h>

#define FORCE_CLUSTERS 0

namespace {

constexpr int HQ = 32, HKV = 8, SEQ = 2048, DH = 128, NGK = 2, GRP = SEQ / NGK;
constexpr int BN = 128, NBLK = SEQ / BN;
constexpr int TILE_BYTES = BN * DH * 2;
constexpr int NS = 6;
constexpr int NST = NS / 2;
constexpr int STAGE_BYTES = 2 * TILE_BYTES;
constexpr int NTILES = HQ * SEQ / 256;
constexpr int TILES_PER_HEAD = NTILES / HKV;
constexpr int QBUF_BYTES = 128 * DH * 2;
constexpr int SMEM_BYTES = NS * TILE_BYTES + QBUF_BYTES + 2048;
constexpr int UNITS_PER_HEAD = 2 * NBLK;
constexpr int ITEMS_PER_UNIT = 32;
constexpr int NITEMS = HKV * UNITS_PER_HEAD * ITEMS_PER_UNIT;
constexpr int ITEMS_PER_CHUNK = 16;
constexpr int NCHUNKS = NITEMS / ITEMS_PER_CHUNK;
constexpr int MIN_LIGHT = 6;
constexpr int MAX_CHUNKS_PER_CTA = (NCHUNKS + 2 * MIN_LIGHT - 1) / (2 * MIN_LIGHT);
constexpr int NIN = 4;
constexpr int NFIRST = 3;
constexpr int LOADER_DELAY = 2000;
constexpr int PIN_J = 7;
constexpr float SCALE_LOG2 = 0.08838834764831845f * 1.4426950408889634f;
constexpr float L_MIN = 9.094947017729282e-13f, L_MAX = 1099511627776.0f;

__device__ __align__(1024) uint4 g_kv[2 * HKV * NBLK * (TILE_BYTES / 16)];
__device__ __align__(128) unsigned int g_cnt[HKV * UNITS_PER_HEAD];
__device__ unsigned int g_done;

__device__ __forceinline__ uint32_t smem_u32(const void* p) { return (uint32_t)__cvta_generic_to_shared(p); }

__device__ __forceinline__ uint4 ld_shared_v4(uint32_t a) {
    uint4 r;
    asm volatile("ld.shared.v4.u32 {%0, %1, %2, %3}, [%4];" : "=r"(r.x), "=r"(r.y), "=r"(r.z), "=r"(r.w) : "r"(a) : "memory");
    return r;
}
__device__ __forceinline__ void mbar_init(uint32_t a, uint32_t cnt) {
    asm volatile("mbarrier.init.shared::cta.b64 [%0], %1;" ::"r"(a), "r"(cnt) : "memory");
}
__device__ __forceinline__ void mbar_expect_tx(uint32_t a, uint32_t bytes) {
    asm volatile("mbarrier.arrive.expect_tx.shared::cta.b64 _, [%0], %1;" ::"r"(a), "r"(bytes) : "memory");
}
__device__ __forceinline__ void mbar_wait(uint32_t a, uint32_t parity) {
    asm volatile(
        "{\n"
        ".reg .pred p;\n"
        ".reg .u32 n;\n"
        "mbarrier.try_wait.parity.shared::cta.b64 p, [%0], %1;\n"
        "@p bra WAIT_DONE;\n"
        "mov.u32 n, 0;\n"
        "WAIT_LOOP:\n"
        "mbarrier.try_wait.parity.shared::cta.b64 p, [%0], %1;\n"
        "@p bra WAIT_DONE;\n"
        "add.u32 n, n, 1;\n"
        "setp.lt.u32 p, n, 0x1000000;\n"
        "@p bra WAIT_LOOP;\n"
        "trap;\n"
        "WAIT_DONE:\n"
        "}\n" ::"r"(a), "r"(parity) : "memory");
}
__device__ __forceinline__ void mbar_wait_sleep(uint32_t a, uint32_t parity) {
    asm volatile(
        "{\n"
        ".reg .pred p;\n"
        ".reg .u32 n;\n"
        "mov.u32 n, 0;\n"
        "WAIT_LOOP:\n"
        "mbarrier.try_wait.parity.shared::cta.b64 p, [%0], %1, 4000;\n"
        "@p bra WAIT_DONE;\n"
        "add.u32 n, n, 1;\n"
        "setp.lt.u32 p, n, 0x100000;\n"
        "@p bra WAIT_LOOP;\n"
        "trap;\n"
        "WAIT_DONE:\n"
        "}\n" ::"r"(a), "r"(parity) : "memory");
}
__device__ __forceinline__ uint32_t mbar_test(uint32_t a, uint32_t parity) {
    uint32_t ok;
    asm volatile("{\n.reg .pred p;\nmbarrier.test_wait.parity.shared::cta.b64 p, [%1], %2;\nselp.u32 %0, 1, 0, p;\n}\n"
                 : "=r"(ok) : "r"(a), "r"(parity) : "memory");
    return ok;
}
__device__ __forceinline__ void mbar_arrive(uint32_t a) {
    asm volatile("mbarrier.arrive.shared::cta.b64 _, [%0];" ::"r"(a) : "memory");
}
__device__ __forceinline__ uint32_t mapa(uint32_t a, uint32_t cta) {
    uint32_t r; asm("mapa.shared::cluster.u32 %0, %1, %2;" : "=r"(r) : "r"(a), "r"(cta)); return r;
}
__device__ __forceinline__ void mbar_arrive_remote(uint32_t ra) {
    asm volatile("mbarrier.arrive.shared::cluster.b64 _, [%0];" ::"r"(ra) : "memory");
}
__device__ __forceinline__ void bulk_load(uint32_t dst, const void* src, uint32_t bytes, uint32_t bar) {
    asm volatile("cp.async.bulk.shared::cluster.global.mbarrier::complete_tx::bytes [%0], [%1], %2, [%3];"
        ::"r"(dst), "l"(src), "r"(bytes), "r"(bar) : "memory");
}
__device__ __forceinline__ void bulk_load_hint(uint32_t dst, const void* src, uint32_t bytes, uint32_t bar, uint64_t pol) {
    asm volatile("cp.async.bulk.shared::cluster.global.mbarrier::complete_tx::bytes.L2::cache_hint [%0], [%1], %2, [%3], %4;"
        ::"r"(dst), "l"(src), "r"(bytes), "r"(bar), "l"(pol) : "memory");
}
__device__ __forceinline__ void bulk_load_mc(uint32_t dst, const void* src, uint32_t bytes, uint32_t bar, uint16_t mask) {
    asm volatile("cp.async.bulk.shared::cluster.global.mbarrier::complete_tx::bytes.multicast::cluster [%0], [%1], %2, [%3], %4;"
        ::"r"(dst), "l"(src), "r"(bytes), "r"(bar), "h"(mask) : "memory");
}
__device__ __forceinline__ void bulk_store(void* dst, uint32_t src, uint32_t bytes) {
    asm volatile("cp.async.bulk.global.shared::cta.bulk_group [%0], [%1], %2;" ::"l"(dst), "r"(src), "r"(bytes) : "memory");
}
__device__ __forceinline__ void tma_load_2d(uint32_t dst, const CUtensorMap* map, int c0, int c1, uint32_t bar) {
    asm volatile("cp.async.bulk.tensor.2d.shared::cluster.global.mbarrier::complete_tx::bytes [%0], [%1, {%3, %4}], [%2];"
        ::"r"(dst), "l"(map), "r"(bar), "r"(c0), "r"(c1) : "memory");
}
__device__ __forceinline__ void cluster_arrive() { asm volatile("barrier.cluster.arrive.relaxed.aligned;" ::: "memory"); }
__device__ __forceinline__ void cluster_arrive_release() { asm volatile("barrier.cluster.arrive.release.aligned;" ::: "memory"); }
__device__ __forceinline__ void cluster_wait() { asm volatile("barrier.cluster.wait.aligned;" ::: "memory"); }
__device__ __forceinline__ void wg_fence() { asm volatile("wgmma.fence.sync.aligned;" ::: "memory"); }
__device__ __forceinline__ void wg_commit() { asm volatile("wgmma.commit_group.sync.aligned;" ::: "memory"); }
template <int N> __device__ __forceinline__ void wg_wait() { asm volatile("wgmma.wait_group.sync.aligned %0;" ::"n"(N) : "memory"); }
__device__ __forceinline__ void bar_sync(int id, int n) { asm volatile("bar.sync %0, %1;" ::"r"(id), "r"(n) : "memory"); }
__device__ __forceinline__ void bar_arrive(int id, int n) { asm volatile("bar.arrive %0, %1;" ::"r"(id), "r"(n) : "memory"); }

__device__ __forceinline__ float ex2(float x) { float y; asm("ex2.approx.ftz.f32 %0, %1;" : "=f"(y) : "f"(x)); return y; }
__device__ __forceinline__ uint32_t pack_bf16(float lo, float hi) {
    uint32_t r; asm("cvt.rn.bf16x2.f32 %0, %1, %2;" : "=r"(r) : "f"(hi), "f"(lo)); return r;
}
__device__ __forceinline__ uint32_t bf2_sub(uint32_t a, uint32_t b) { uint32_t r; asm("sub.rn.bf16x2 %0, %1, %2;" : "=r"(r) : "r"(a), "r"(b)); return r; }
__device__ __forceinline__ uint32_t bf2_mul(uint32_t a, uint32_t b) { uint32_t r; asm("mul.rn.bf16x2 %0, %1, %2;" : "=r"(r) : "r"(a), "r"(b)); return r; }
__device__ __forceinline__ uint32_t bf2_fma(uint32_t a, uint32_t b, uint32_t c) { uint32_t r; asm("fma.rn.bf16x2 %0, %1, %2, %3;" : "=r"(r) : "r"(a), "r"(b), "r"(c)); return r; }

#define F8(a, i) "+f"(a[i]), "+f"(a[i + 1]), "+f"(a[i + 2]), "+f"(a[i + 3]), "+f"(a[i + 4]), "+f"(a[i + 5]), "+f"(a[i + 6]), "+f"(a[i + 7])
#define F64(a) F8(a, 0), F8(a, 8), F8(a, 16), F8(a, 24), F8(a, 32), F8(a, 40), F8(a, 48), F8(a, 56)

template <int TB>
__device__ __forceinline__ void wgmma_rs(float (&d)[64], uint32_t a0, uint32_t a1, uint32_t a2, uint32_t a3, uint64_t desc, int scale_d) {
    asm volatile(
        "{\n.reg .pred p;\nsetp.ne.b32 p, %69, 0;\n"
        "wgmma.mma_async.sync.aligned.m64n128k16.f32.bf16.bf16 "
        "{%0,%1,%2,%3,%4,%5,%6,%7,%8,%9,%10,%11,%12,%13,%14,%15,"
        "%16,%17,%18,%19,%20,%21,%22,%23,%24,%25,%26,%27,%28,%29,%30,%31,"
        "%32,%33,%34,%35,%36,%37,%38,%39,%40,%41,%42,%43,%44,%45,%46,%47,"
        "%48,%49,%50,%51,%52,%53,%54,%55,%56,%57,%58,%59,%60,%61,%62,%63},"
        "{%64,%65,%66,%67}, %68, p, 1, 1, %70;\n}\n"
        : F64(d)
        : "r"(a0), "r"(a1), "r"(a2), "r"(a3), "l"(desc), "r"(scale_d), "n"(TB));
}
__device__ __forceinline__ void fence_regs(float (&d)[64]) {
#pragma unroll
    for (int i = 0; i < 64; i++) asm volatile("" : "+f"(d[i])::"memory");
}
__device__ __forceinline__ void fence_regs(uint32_t (&d)[32]) {
#pragma unroll
    for (int i = 0; i < 32; i++) asm volatile("" : "+r"(d[i])::"memory");
}

struct DqItem { int kv, head, p, tok; };
__device__ __forceinline__ DqItem item_decode(int it, int h0, int h0inv) {
    DqItem d;
    const int su = it / ITEMS_PER_UNIT, part = it % ITEMS_PER_UNIT;
    if (su < UNITS_PER_HEAD * h0) { d.p = (su * h0inv) >> 16; d.head = su - d.p * h0; }
    else { const int x = su - UNITS_PER_HEAD * h0; d.head = h0 + x / UNITS_PER_HEAD; d.p = x % UNITS_PER_HEAD; }
    int blk;
    if (d.p == 0) { d.kv = 0; blk = 0; }
    else if (d.p == UNITS_PER_HEAD - 1) { d.kv = 1; blk = NBLK - 1; }
    else if (d.p & 1) { d.kv = 0; blk = (d.p + 1) >> 1; }
    else { d.kv = 1; blk = (d.p >> 1) - 1; }
    d.tok = blk * BN + part * 4;
    return d;
}
struct DqPtrs {
    const int* qk; const int* qv;
    const __nv_bfloat16 *ks, *kz, *vs, *vz;
};
__device__ __forceinline__ uint8_t* kv_tile(int kv, int head, int blk) {
    return reinterpret_cast<uint8_t*>(g_kv) + (size_t)((kv * HKV + head) * NBLK + blk) * TILE_BYTES;
}
__device__ __forceinline__ uint32_t codes_bf2(int a, int b) { return pack_bf16(__int2float_rn(a), __int2float_rn(b)); }
__device__ __forceinline__ void k_scale_split(uint32_t s, uint32_t& hi, uint32_t& lo) {
    const float f0 = __uint_as_float(s << 16) * SCALE_LOG2, f1 = __uint_as_float(s & 0xffff0000u) * SCALE_LOG2;
    hi = pack_bf16(f0, f1);
    lo = pack_bf16(f0 - __uint_as_float(hi << 16), f1 - __uint_as_float(hi & 0xffff0000u));
}
__device__ __forceinline__ uint32_t dq_k(int a, int b, uint32_t z, uint32_t hi, uint32_t lo) {
    const uint32_t t = bf2_sub(codes_bf2(a, b), z);
    return bf2_fma(t, hi, bf2_mul(t, lo));
}
__device__ __forceinline__ uint32_t dq_v(int a, int b, uint32_t z, uint32_t s) { return bf2_mul(bf2_sub(codes_bf2(a, b), z), s); }

__device__ __forceinline__ void ldg_stream2(int& a, int& b, const int* p, uint64_t pol) {
    asm volatile("ld.global.nc.L1::no_allocate.L2::cache_hint.v2.s32 {%0, %1}, [%2], %3;" : "=r"(a), "=r"(b) : "l"(p), "l"(pol));
}
__device__ __forceinline__ void ldg_stream4(int& a, int& b, int& c, int& d, const int* p, uint64_t pol) {
    asm volatile("ld.global.nc.L1::no_allocate.L2::cache_hint.v4.s32 {%0, %1, %2, %3}, [%4], %5;" : "=r"(a), "=r"(b), "=r"(c), "=r"(d) : "l"(p), "l"(pol));
}
__device__ __forceinline__ void dq_load(int (&v)[16], uint32_t (&zs)[4], const DqItem& d, int lane, const DqPtrs& g, uint64_t pol) {
    if (d.kv == 0) {
        const int* src = g.qk + (size_t)(d.head * SEQ + d.tok) * DH + 4 * lane;
#pragma unroll
        for (int r = 0; r < 4; r++) ldg_stream4(v[4 * r], v[4 * r + 1], v[4 * r + 2], v[4 * r + 3], src + r * DH, pol);
        const int so = (d.head * NGK + d.tok / GRP) * DH + 4 * lane;
        const uint2 zz = __ldg(reinterpret_cast<const uint2*>(g.kz + so)), ss = __ldg(reinterpret_cast<const uint2*>(g.ks + so));
        zs[0] = zz.x; zs[1] = zz.y; zs[2] = ss.x; zs[3] = ss.y;
    } else {
        const int tk = d.head * SEQ + d.tok + (lane >> 4);
        const int* src = g.qv + (size_t)tk * DH + 32 * ((lane & 15) >> 2) + 2 * (lane & 3);
        const unsigned short* z = reinterpret_cast<const unsigned short*>(g.vz) + tk;
        const unsigned short* sc = reinterpret_cast<const unsigned short*>(g.vs) + tk;
#pragma unroll
        for (int r = 0; r < 2; r++) {
#pragma unroll
            for (int c = 0; c < 4; c++) ldg_stream2(v[8 * r + 2 * c], v[8 * r + 2 * c + 1], src + 2 * r * DH + 8 * c, pol);
            zs[r] = __ldg(z + 2 * r); zs[2 + r] = __ldg(sc + 2 * r);
        }
    }
}
__device__ __forceinline__ void dq_convert_store(const int (&v)[16], const uint32_t (&zs)[4], const DqItem& d, int lane) {
    const int tr = d.tok % BN;
    uint8_t* tile = kv_tile(d.kv, d.head, d.tok / BN);
    if (d.kv == 0) {
        uint32_t h0, l0, h1, l1;
        k_scale_split(zs[2], h0, l0); k_scale_split(zs[3], h1, l1);
        uint8_t* dst = tile + (lane >> 4) * (TILE_BYTES / 2) + (lane & 1) * 8 + tr * 128;
        const int ch = (lane & 15) >> 1;
#pragma unroll
        for (int r = 0; r < 4; r++)
            *reinterpret_cast<uint2*>(dst + r * 128 + ((ch ^ ((tr + r) & 7)) << 4)) =
                make_uint2(dq_k(v[4 * r], v[4 * r + 1], zs[0], h0, l0), dq_k(v[4 * r + 2], v[4 * r + 3], zs[1], h1, l1));
    } else {
        const int i = (lane & 15) >> 2, ch = 4 * (i & 1) + (lane & 3), t0 = tr + (lane >> 4);
        uint8_t* dst = tile + (i >> 1) * (TILE_BYTES / 2) + t0 * 128;
#pragma unroll
        for (int r = 0; r < 2; r++) {
            const uint32_t z = zs[r] * 0x10001u, s = zs[2 + r] * 0x10001u;
            *reinterpret_cast<uint4*>(dst + 2 * r * 128 + ((ch ^ ((t0 + 2 * r) & 7)) << 4)) =
                make_uint4(dq_v(v[8 * r], v[8 * r + 1], z, s), dq_v(v[8 * r + 2], v[8 * r + 3], z, s),
                           dq_v(v[8 * r + 4], v[8 * r + 5], z, s), dq_v(v[8 * r + 6], v[8 * r + 7], z, s));
        }
    }
}
__device__ __forceinline__ void dq_signal(const DqItem& d, int lane) {
    asm volatile("fence.proxy.async.global;" ::: "memory");
    __syncwarp();
    if (lane == 0) asm volatile("red.release.gpu.global.add.u32 [%0], 1;" ::"l"(g_cnt + d.head * UNITS_PER_HEAD + d.p) : "memory");
}
__device__ __forceinline__ void dequant_loop(int it, int stride, int end, int h0, int h0inv, int lane, const DqPtrs& g, uint64_t pol) {
    if (it >= end) return;
    DqItem d = item_decode(it, h0, h0inv);
    int v[16]; uint32_t zs[4];
    dq_load(v, zs, d, lane, g, pol);
    while (true) {
        dq_convert_store(v, zs, d, lane);
        const DqItem dc = d;
        it += stride;
        const bool more = it < end;
        if (more) {
            d = item_decode(it, h0, h0inv);
            dq_load(v, zs, d, lane, g, pol);
        }
        dq_signal(dc, lane);
        if (!more) break;
    }
}
__device__ __forceinline__ void dq_bulk_zs(uint32_t (&zs)[16], uint32_t zi, int lane, const DqPtrs& g) {
    if (!(zi >> 31)) {
        const uint32_t so = zi + 4 * lane;
        const uint2 zz = __ldg(reinterpret_cast<const uint2*>(g.kz + so)), ss = __ldg(reinterpret_cast<const uint2*>(g.ks + so));
        zs[0] = zz.x; zs[1] = zz.y; zs[2] = ss.x; zs[3] = ss.y;
    } else {
        const uint4* z = reinterpret_cast<const uint4*>(g.vz + (zi & 0x7fffffffu));
        const uint4* s = reinterpret_cast<const uint4*>(g.vs + (zi & 0x7fffffffu));
        const uint4 z0 = __ldg(z), z1 = __ldg(z + 1), s0 = __ldg(s), s1 = __ldg(s + 1);
        zs[0] = z0.x; zs[1] = z0.y; zs[2] = z0.z; zs[3] = z0.w; zs[4] = z1.x; zs[5] = z1.y; zs[6] = z1.z; zs[7] = z1.w;
        zs[8] = s0.x; zs[9] = s0.y; zs[10] = s0.z; zs[11] = s0.w; zs[12] = s1.x; zs[13] = s1.y; zs[14] = s1.z; zs[15] = s1.w;
    }
}
__device__ __forceinline__ void dq_bulk_convert(const int (&v)[64], const uint32_t (&zs)[16], int kv, uint32_t dst, int lane) {
    if (kv == 0) {
        uint32_t h0, l0, h1, l1;
        k_scale_split(zs[2], h0, l0); k_scale_split(zs[3], h1, l1);
        const uint32_t a = dst + (lane >> 4) * 2048 + (lane & 1) * 8;
        const int ch = (lane & 15) >> 1;
#pragma unroll
        for (int r = 0; r < 16; r++)
            asm volatile("st.shared.v2.u32 [%0], {%1, %2};" ::"r"(a + r * 128 + ((ch ^ (r & 7)) << 4)),
                         "r"(dq_k(v[4 * r], v[4 * r + 1], zs[0], h0, l0)), "r"(dq_k(v[4 * r + 2], v[4 * r + 3], zs[1], h1, l1)) : "memory");
    } else {
        const int i = lane >> 3, c = (lane & 7) >> 1, ch = 4 * (i & 1) + 2 * (lane & 1);
        const uint32_t a = dst + (i >> 1) * 2048 + 4 * c;
#pragma unroll
        for (int r = 0; r < 16; r++) {
            const uint32_t sel = (r & 1) ? 0x3232u : 0x1010u;
            const uint32_t z = __byte_perm(zs[r >> 1], 0, sel), s = __byte_perm(zs[8 + (r >> 1)], 0, sel);
            asm volatile("st.shared.u32 [%0], %1;" ::"r"(a + r * 128 + ((ch ^ (r & 7)) << 4)), "r"(dq_v(v[4 * r], v[4 * r + 1], z, s)) : "memory");
            asm volatile("st.shared.u32 [%0], %1;" ::"r"(a + r * 128 + (((ch + 1) ^ (r & 7)) << 4)), "r"(dq_v(v[4 * r + 2], v[4 * r + 3], z, s)) : "memory");
        }
    }
}

template <int V> struct IC { static constexpr int value = V; };
struct Ring {
    uint32_t slot, phase, desc;
    __device__ __forceinline__ void advance() {
        slot += 1; desc += STAGE_BYTES >> 4;
        if (slot == NST) { slot = 0; desc -= NST * (STAGE_BYTES >> 4); phase ^= 1; }
    }
};

__device__ __forceinline__ void load_q(uint32_t (&qf)[32], uint32_t qrow, uint32_t qsw) {
#pragma unroll
    for (int kk = 0; kk < 8; kk++)
        asm volatile("ldmatrix.sync.aligned.m8n8.x4.shared.b16 {%0, %1, %2, %3}, [%4];"
                     : "=r"(qf[4 * kk]), "=r"(qf[4 * kk + 1]), "=r"(qf[4 * kk + 2]), "=r"(qf[4 * kk + 3])
                     : "r"(qrow + (kk >> 2) * (QBUF_BYTES / 2) + (qsw ^ ((kk & 3) << 5))) : "memory");
}
__device__ __forceinline__ uint32_t tile_desc(uint32_t addr) { return (addr & 0x3FFFFu) >> 4; }
__device__ __forceinline__ uint32_t k_desc(uint32_t d) { return d | (1u << 16); }
__device__ __forceinline__ uint32_t v_desc(uint32_t d) { return d | (1024u << 16); }
__device__ __forceinline__ void issue_qk(float (&S)[64], const uint32_t (&qf)[32], uint32_t lo) {
    const uint64_t hi = (uint64_t)(64u | (1u << 30)) << 32;
#pragma unroll
    for (int kk = 0; kk < 8; kk++)
        wgmma_rs<0>(S, qf[4 * kk], qf[4 * kk + 1], qf[4 * kk + 2], qf[4 * kk + 3],
                    hi | (uint64_t)(lo + (kk >> 2) * 1024 + (kk & 3) * 2), kk != 0);
}
__device__ __forceinline__ void issue_pv(float (&O)[64], const uint32_t (&P)[32], uint32_t lo, int acc) {
    const uint64_t hi = (uint64_t)(64u | (1u << 30)) << 32;
#pragma unroll
    for (int kk = 0; kk < 8; kk++)
        wgmma_rs<1>(O, P[4 * kk], P[4 * kk + 1], P[4 * kk + 2], P[4 * kk + 3], hi | (uint64_t)(lo + kk * 128), kk != 0 ? 1 : acc);
}
template <int J0, int J1>
__device__ __forceinline__ void exp_part(float (&S)[64], float (&acc)[4]) {
#pragma unroll
    for (int j = J0; j < J1; j++) {
        S[4 * j + 0] = ex2(S[4 * j + 0]);
        S[4 * j + 1] = ex2(S[4 * j + 1]);
        S[4 * j + 2] = ex2(S[4 * j + 2]);
        S[4 * j + 3] = ex2(S[4 * j + 3]);
        if (j == 0) { acc[0] = S[0]; acc[1] = S[1]; acc[2] = S[2]; acc[3] = S[3]; }
        else { acc[0] += S[4 * j + 0]; acc[1] += S[4 * j + 1]; acc[2] += S[4 * j + 2]; acc[3] += S[4 * j + 3]; }
    }
}
__device__ __forceinline__ void cvt_p(const float (&S)[64], uint32_t (&P)[32]) {
#pragma unroll
    for (int j = 0; j < 16; j++) {
        P[2 * j] = pack_bf16(S[4 * j], S[4 * j + 1]);
        P[2 * j + 1] = pack_bf16(S[4 * j + 2], S[4 * j + 3]);
    }
}
__device__ __forceinline__ bool finish_l(float l0, float l1, float& i0, float& i1) {
    l0 += __shfl_xor_sync(0xffffffffu, l0, 1); l1 += __shfl_xor_sync(0xffffffffu, l1, 1);
    l0 += __shfl_xor_sync(0xffffffffu, l0, 2); l1 += __shfl_xor_sync(0xffffffffu, l1, 2);
    asm("rcp.approx.ftz.f32 %0, %1;" : "=f"(i0) : "f"(l0));
    asm("rcp.approx.ftz.f32 %0, %1;" : "=f"(i1) : "f"(l1));
    return l0 >= L_MIN && l0 <= L_MAX && l1 >= L_MIN && l1 <= L_MAX;
}
__device__ __forceinline__ bool store_o(const float (&O)[64], float i0, float i1, __nv_bfloat16* __restrict__ orow) {
    float c0 = 0.f, c1 = 0.f, c2 = 0.f, c3 = 0.f;
#pragma unroll
    for (int i = 0; i < 4; i++) {
        uint4 a, b;
        a.x = pack_bf16(O[16 * i + 0] * i0, O[16 * i + 1] * i0);
        a.y = pack_bf16(O[16 * i + 4] * i0, O[16 * i + 5] * i0);
        a.z = pack_bf16(O[16 * i + 8] * i0, O[16 * i + 9] * i0);
        a.w = pack_bf16(O[16 * i + 12] * i0, O[16 * i + 13] * i0);
        b.x = pack_bf16(O[16 * i + 2] * i1, O[16 * i + 3] * i1);
        b.y = pack_bf16(O[16 * i + 6] * i1, O[16 * i + 7] * i1);
        b.z = pack_bf16(O[16 * i + 10] * i1, O[16 * i + 11] * i1);
        b.w = pack_bf16(O[16 * i + 14] * i1, O[16 * i + 15] * i1);
        *reinterpret_cast<uint4*>(orow + 32 * i) = a;
        *reinterpret_cast<uint4*>(orow + 8 * DH + 32 * i) = b;
#pragma unroll
        for (int e = 0; e < 16; e += 4) {
            c0 = fmaf(O[16 * i + e], 0.f, c0); c1 = fmaf(O[16 * i + e + 1], 0.f, c1);
            c2 = fmaf(O[16 * i + e + 2], 0.f, c2); c3 = fmaf(O[16 * i + e + 3], 0.f, c3);
        }
    }
    return (c0 + c1) + (c2 + c3) == 0.f;
}

struct Sched {
    int rem;
    int nlight;
    int bulk;
    int h0, h0inv;
    int nhelp;
    int nfirst;
};

__global__ void __cluster_dims__(2, 1, 1) __launch_bounds__(384, 1)
attn_kernel(const __grid_constant__ CUtensorMap qmap, const int* __restrict__ qk, const int* __restrict__ qv,
            const __nv_bfloat16* __restrict__ ks, const __nv_bfloat16* __restrict__ kz,
            const __nv_bfloat16* __restrict__ vs, const __nv_bfloat16* __restrict__ vz,
            __nv_bfloat16* __restrict__ out, const Sched sc) {
    extern __shared__ __align__(1024) uint8_t smem_raw[];
    const uint32_t sb = smem_u32(smem_raw);
    const uint32_t qbuf = sb + NS * TILE_BYTES;
    const uint32_t bar_full = qbuf + QBUF_BYTES, bar_empty = bar_full + 8 * NS;
    const uint32_t bar_qfull = bar_empty + 8 * NS, bar_qempty = bar_qfull + 8, pin_addr = bar_qempty + 8;
    const uint32_t bar_dfull = pin_addr + 8;
    const uint32_t bar_bempty = bar_dfull + 8;
    const uint32_t bar_rfull = bar_bempty + 8 * NIN, bar_rempty = bar_rfull + 16;
    const uint32_t bar_bfull = bar_rempty + 16, bar_bdone = bar_bfull + 8 * MAX_CHUNKS_PER_CTA;
    const uint32_t chunk_tab = bar_full + 1280;
    volatile uint8_t* redo = smem_raw + NS * TILE_BYTES + QBUF_BYTES + 1024;
    const int wg = __shfl_sync(0xffffffffu, threadIdx.x >> 7, 0);
    const int warp = __shfl_sync(0xffffffffu, (threadIdx.x >> 5) & 3, 0);
    const int lane = threadIdx.x & 31;
    uint32_t rank; asm("mov.u32 %0, %%cluster_ctarank;" : "=r"(rank));
    const int cluster_id = blockIdx.x >> 1, nclusters = gridDim.x >> 1;

    const bool light = sc.bulk && cluster_id >= sc.rem;
    const int h0 = sc.h0, h0inv = sc.h0inv;
    const int chunk0 = sc.nfirst / ITEMS_PER_CHUNK + (int)blockIdx.x - 2 * sc.rem, chunk_stride = 2 * sc.nlight;
    const int nchunks = light ? (NCHUNKS - chunk0 + chunk_stride - 1) / chunk_stride : 0;
    const DqPtrs dq{qk, qv, ks, kz, vs, vz};
    uint64_t pol;
    asm volatile("createpolicy.fractional.L2::evict_first.b64 %0, 1.0;" : "=l"(pol));
    const int gwarp = wg * 4 + warp;

    if (gwarp == 0) {
        if (sb & 1023u) __trap();
        if (lane < NST) { mbar_init(bar_full + 8 * lane, 1); mbar_init(bar_empty + 8 * lane, 4); }
        if (lane == 8) { mbar_init(bar_qfull, 1); mbar_init(bar_qempty, 8); mbar_init(bar_dfull, 1); }
        if (lane == 9 || lane == 10) { mbar_init(bar_rfull + 8 * (lane - 9), 1); mbar_init(bar_rempty + 8 * (lane - 9), 2); }
        if (light) {
            if (lane >= 16 && lane < 16 + NIN) mbar_init(bar_bempty + 8 * (lane - 16), 4);
            for (int s = lane; s < nchunks; s += 32) {
                mbar_init(bar_bfull + 8 * s, 1); mbar_init(bar_bdone + 8 * s, 4);
                const DqItem d = item_decode((chunk0 + s * chunk_stride) * ITEMS_PER_CHUNK, h0, h0inv);
                const uint32_t w0 = (uint32_t)(kv_tile(d.kv, d.head, d.tok / BN) - reinterpret_cast<uint8_t*>(g_kv)) + (d.tok % BN) * 128;
                const uint32_t w1 = d.kv ? (0x80000000u | (uint32_t)(d.head * SEQ + d.tok)) : (uint32_t)((d.head * NGK + d.tok / GRP) * DH);
                asm volatile("st.shared.v4.u32 [%0], {%1, %2, %3, %4};" ::"r"(chunk_tab + 16 * s), "r"(w0), "r"(w1),
                             "r"((uint32_t)((d.head * SEQ + d.tok) * DH)), "r"((uint32_t)(d.head * UNITS_PER_HEAD + d.p)) : "memory");
            }
        }
        asm volatile("fence.mbarrier_init.release.cluster;\nfence.acq_rel.cta;" ::: "memory");
        __syncwarp();
        if (light && lane == 0) {
            mbar_expect_tx(bar_qfull, QBUF_BYTES);
            tma_load_2d(qbuf, &qmap, 0, cluster_id * 256 + rank * 128, bar_qfull);
            tma_load_2d(qbuf + QBUF_BYTES / 2, &qmap, 64, cluster_id * 256 + rank * 128, bar_qfull);
        }
        __syncwarp();
        cluster_arrive();
        if (light) {
            if (lane == 0) {
                const long long t0 = clock64();
                while (clock64() - t0 < LOADER_DELAY) {}
                for (int k = 0; k < nchunks; k++) {
                    const int slot = k % NIN;
                    const uint4 e = ld_shared_v4(chunk_tab + 16 * k);
                    mbar_wait_sleep(bar_bempty + 8 * slot, ((k / NIN) & 1) ^ 1);
                    mbar_expect_tx(bar_bfull + 8 * k, TILE_BYTES);
                    bulk_load_hint(sb + slot * TILE_BYTES, ((e.y >> 31) ? qv : qk) + e.z, TILE_BYTES, bar_bfull + 8 * k, pol);
                }
            }
            __syncwarp();
        }
        cluster_wait();
        if (!light && lane == 0) {
            mbar_expect_tx(bar_dfull, STAGE_BYTES);
            bulk_load_mc(sb + (NST - 1) * STAGE_BYTES + rank * TILE_BYTES, qk + (size_t)((cluster_id / TILES_PER_HEAD) * SEQ + rank * 64) * DH,
                         TILE_BYTES, bar_dfull, (uint16_t)3);
            mbar_expect_tx(bar_qfull, QBUF_BYTES);
            tma_load_2d(qbuf, &qmap, 0, cluster_id * 256 + rank * 128, bar_qfull);
            tma_load_2d(qbuf + QBUF_BYTES / 2, &qmap, 64, cluster_id * 256 + rank * 128, bar_qfull);
        }
        __syncwarp();
    } else {
        cluster_arrive();
        if (light || wg != 0) cluster_wait();
        if (light && gwarp == 1) {
            if (lane == 0) {
                for (int sig = 0; sig < nchunks;) {
                    mbar_wait_sleep(bar_bdone + 8 * sig, 0);
                    int m = 1;
                    while (m < 4 && sig + m < nchunks && mbar_test(bar_bdone + 8 * (sig + m), 0)) m++;
                    asm volatile("fence.acq_rel.gpu;" ::: "memory");
                    for (int i = 0; i < m; i++) {
                        const uint4 e = ld_shared_v4(chunk_tab + 16 * (sig + i));
                        asm volatile("red.relaxed.gpu.global.add.u32 [%0], %1;" ::"l"(g_cnt + e.w), "r"(ITEMS_PER_CHUNK) : "memory");
                    }
                    sig += m;
                }
            }
            __syncwarp();
        } else if (light) {
            const uint32_t obuf = sb + NIN * TILE_BYTES + (gwarp - 2) * 4096;
            const int nq = 4 * nchunks;
            int j = gwarp - 2, kprev = -1;
            uint32_t ooff = 0, zi = 0, zs[16];
            auto prepare = [&](int jj, uint32_t& ooff_, uint32_t& zi_, uint32_t (&zs_)[16]) {
                const uint4 e = ld_shared_v4(chunk_tab + 16 * (jj >> 2));
                ooff_ = e.x + (jj & 3) * 2048;
                zi_ = e.y + ((e.y >> 31) ? (jj & 3) * 16 : 0);
                dq_bulk_zs(zs_, zi_, lane, dq);
            };
            if (j < nq) prepare(j, ooff, zi, zs);
            while (j < nq) {
                const int k = j >> 2, slot = k % NIN;
                mbar_wait(bar_bfull + 8 * k, 0);
                int v[64];
                const uint32_t src = sb + slot * TILE_BYTES + (j & 3) * 8192 + lane * 16;
#pragma unroll
                for (int r = 0; r < 16; r++)
                    asm volatile("ld.shared.v4.s32 {%0, %1, %2, %3}, [%4];" : "=r"(v[4 * r]), "=r"(v[4 * r + 1]), "=r"(v[4 * r + 2]), "=r"(v[4 * r + 3])
                                 : "r"(src + r * 512) : "memory");
                uint32_t ooffn = 0, zin = 0, zsn[16];
                if (j + 10 < nq) prepare(j + 10, ooffn, zin, zsn);
                __syncwarp();
                if (lane == 0) {
                    mbar_arrive(bar_bempty + 8 * slot);
                    if (kprev >= 0) {
                        asm volatile("cp.async.bulk.wait_group 0;" ::: "memory");
                        mbar_arrive(bar_bdone + 8 * kprev);
                    }
                }
                __syncwarp();
                dq_bulk_convert(v, zs, zi >> 31, obuf, lane);
                asm volatile("fence.proxy.async.shared::cta;" ::: "memory");
                __syncwarp();
                if (lane == 0) {
                    uint8_t* o = reinterpret_cast<uint8_t*>(g_kv) + ooff;
                    bulk_store(o, obuf, 2048);
                    bulk_store(o + TILE_BYTES / 2, obuf + 2048, 2048);
                    asm volatile("cp.async.bulk.commit_group;" ::: "memory");
                }
                kprev = k;
                j += 10;
                ooff = ooffn; zi = zin;
#pragma unroll
                for (int i = 0; i < 16; i++) zs[i] = zsn[i];
            }
            if (kprev >= 0 && lane == 0) {
                asm volatile("cp.async.bulk.wait_group 0;" ::: "memory");
                mbar_arrive(bar_bdone + 8 * kprev);
            }
            __syncwarp();
        }
    }
    if (light) { cluster_arrive_release(); cluster_wait(); }

    if (wg == 0) {
        asm volatile("setmaxnreg.dec.sync.aligned.u32 56;");
        if (warp == 0) {
            uint32_t qphase = 0;
            auto load_qtile = [&](int t) {
                if (lane == 0) {
                    mbar_wait(bar_qempty, qphase);
                    mbar_expect_tx(bar_qfull, QBUF_BYTES);
                    tma_load_2d(qbuf, &qmap, 0, t * 256 + rank * 128, bar_qfull);
                    tma_load_2d(qbuf + QBUF_BYTES / 2, &qmap, 64, t * 256 + rank * 128, bar_qfull);
                }
                __syncwarp();
                qphase ^= 1;
            };
            Ring r{0, 1, 0};
            int vhead = -1;
            uint32_t vmask = 0;
            auto await_unit = [&](int kv, int head, int blk) {
                const int p = kv == 0 ? (blk == 0 ? 0 : 2 * blk - 1) : (blk == NBLK - 1 ? UNITS_PER_HEAD - 1 : 2 * blk + 2);
                if (head != vhead) { vhead = head; vmask = 0; }
                if (!((vmask >> p) & 1)) {
                    uint32_t n = 0;
                    while (true) {
                        unsigned int c;
                        asm volatile("ld.acquire.gpu.global.u32 %0, [%1];" : "=r"(c) : "l"(g_cnt + head * UNITS_PER_HEAD + lane) : "memory");
                        vmask = __ballot_sync(0xffffffffu, c == ITEMS_PER_UNIT);
                        if ((vmask >> p) & 1) break;
                        if (++n > (1u << 22)) __trap();
                    }
                    asm volatile("fence.proxy.async.global;" ::: "memory");
                }
            };
            auto load = [&](int khead, int kblk, int vh, int vblk) {
                if (vh >= 0) await_unit(1, vh, vblk);
                if (khead >= 0) await_unit(0, khead, kblk);
                if (lane == 0) {
                    const uint32_t full = bar_full + 8 * r.slot, dst = sb + r.slot * STAGE_BYTES + rank * (TILE_BYTES / 2);
                    mbar_wait_sleep(bar_empty + 8 * r.slot, r.phase ^ (uint32_t)(!light && r.slot == NST - 1));
                    mbar_expect_tx(full, (khead >= 0 ? TILE_BYTES : 0) + (vh >= 0 ? TILE_BYTES : 0));
                    if (khead >= 0) bulk_load_mc(dst, kv_tile(0, khead, kblk) + rank * (TILE_BYTES / 2), TILE_BYTES / 2, full, (uint16_t)3);
                    if (vh >= 0) bulk_load_mc(dst + TILE_BYTES, kv_tile(1, vh, vblk) + rank * (TILE_BYTES / 2), TILE_BYTES / 2, full, (uint16_t)3);
                }
                __syncwarp();
                r.advance();
            };
            if (light) load(cluster_id / TILES_PER_HEAD, 0, -1, 0);
            else {
                if (lane == 0) mbar_arrive(bar_full);
                __syncwarp();
                r.advance();
            }
            for (int t = cluster_id; t < NTILES; t += nclusters) {
                const int head = t / TILES_PER_HEAD;
                const int tn = t + nclusters;
                for (int j = 0; j < NBLK; j++) {
                    if (j == 4 && tn < NTILES) load_qtile(tn);
                    if (j < NBLK - 1) load(head, j + 1, head, j);
                    else load(tn < NTILES ? tn / TILES_PER_HEAD : -1, 0, head, j);
                }
            }
            if (!light) await_unit(0, cluster_id / TILES_PER_HEAD, 0);
            if (lane == 0) {
                const unsigned int prev = atomicAdd(&g_done, 1u);
                if (prev == gridDim.x - 1) {
                    for (int i = 0; i < HKV * UNITS_PER_HEAD; i++) g_cnt[i] = 0;
                    g_done = 0;
                }
            }
            __syncwarp();
            bar_sync(3, 288);
            uint32_t n = 0;
            for (int t = cluster_id, k = 0; t < NTILES; t += nclusters, k++) {
                if (!redo[k]) continue;
                load_qtile(t);
                if (lane == 0) {
                    for (int j = 0; j < 2 * NBLK; j++, n++) {
                        const uint32_t s = n & 1;
                        mbar_wait(bar_rempty + 8 * s, ((n >> 1) & 1) ^ 1);
                        mbar_expect_tx(bar_rfull + 8 * s, TILE_BYTES);
                        bulk_load(sb + s * TILE_BYTES, kv_tile(j & 1, t / TILES_PER_HEAD, j >> 1), TILE_BYTES, bar_rfull + 8 * s);
                    }
                }
                __syncwarp();
            }
        } else {
            if (!light) {
                dequant_loop(blockIdx.x * 3 + (warp - 1), sc.nhelp, sc.nfirst, h0, h0inv, lane, dq, pol);
                cluster_wait();
            }
        }
        cluster_arrive(); cluster_wait();
    } else {
        asm volatile("setmaxnreg.inc.sync.aligned.u32 224;");
        const int w = wg - 1;
        const int my_bar = 1 + w, other_bar = 2 - w;
        const int row_in_tile = rank * 128 + w * 64 + warp * 16 + (lane >> 2);
        const int coff = (lane & 3) * 8;
        const uint32_t qrow = qbuf + (w * 64 + warp * 16 + (lane & 15)) * 128;
        const uint32_t qsw = ((lane >> 4) ^ (lane & 7)) << 4;
        const uint32_t rem_empty = mapa(bar_empty, warp & 1);
        const bool releaser = lane == 0 && warp < 2;
        uint32_t qf[32], P[32];
        float S[64], O[64];
        float l0 = 0.f, l1 = 0.f, lo0 = 1.f, lo1 = 1.f;
        uint32_t qphase = 0;
        Ring r{0, 0, tile_desc(sb)};
        auto release = [&]() {
            if (releaser) mbar_arrive_remote(rem_empty + 8 * r.slot);
            r.advance();
        };
        auto reload_q = [&]() {
            mbar_wait(bar_qfull, qphase);
            qphase ^= 1;
            load_q(qf, qrow, qsw);
            __syncwarp();
            if (lane == 0) mbar_arrive(bar_qempty);
        };
        auto pin = [&](float x) {
            asm volatile("{\n.reg .pred p;\nsetp.eq.f32 p, %0, 0fBF800000;\n@p st.shared.f32 [%1], %0;\n}\n" ::"f"(x), "r"(pin_addr) : "memory");
        };
        int t = cluster_id, tk = 0;
#pragma unroll
        for (int i = 0; i < 64; i++) { S[i] = 0.f; O[i] = 0.f; }
        if (gwarp == 4) { reinterpret_cast<volatile uint32_t*>(redo)[lane] = 0; reinterpret_cast<volatile uint32_t*>(redo)[lane + 32] = 0; }
        if (w == 1) bar_arrive(1, 256);
        if (!light) {
            const int cw = w * 4 + warp;
            const int so = (cluster_id / TILES_PER_HEAD) * NGK * DH + 4 * lane;
            const uint2 zz = __ldg(reinterpret_cast<const uint2*>(kz + so)), ss = __ldg(reinterpret_cast<const uint2*>(ks + so));
            uint32_t h0_, l0_, h1_, l1_;
            k_scale_split(ss.x, h0_, l0_); k_scale_split(ss.y, h1_, l1_);
            mbar_wait(bar_dfull, 0);
            const uint32_t src = sb + (NST - 1) * STAGE_BYTES + cw * 8192 + lane * 16;
            const uint32_t dst = sb + (lane >> 4) * (TILE_BYTES / 2) + cw * 2048 + (lane & 1) * 8;
            const int ch = (lane & 15) >> 1;
#pragma unroll
            for (int i = 0; i < 16; i++) {
                int a, b, c, d;
                asm volatile("ld.shared.v4.s32 {%0, %1, %2, %3}, [%4];" : "=r"(a), "=r"(b), "=r"(c), "=r"(d) : "r"(src + i * 512) : "memory");
                asm volatile("st.shared.v2.u32 [%0], {%1, %2};" ::"r"(dst + i * 128 + ((ch ^ (i & 7)) << 4)),
                             "r"(dq_k(a, b, zz.x, h0_, l0_)), "r"(dq_k(c, d, zz.y, h1_, l1_)) : "memory");
            }
            asm volatile("fence.proxy.async.shared::cta;" ::: "memory");
            bar_sync(4, 256);
            if (releaser) mbar_arrive_remote(rem_empty + 8 * (NST - 1));
        }
        reload_q();
        {
            if (light) mbar_wait(bar_full, 0);
            bar_sync(my_bar, 256);
            wg_fence();
            issue_qk(S, qf, k_desc(r.desc));
            wg_commit();
            bar_arrive(other_bar, 256);
            wg_wait<0>();
            fence_regs(S);
            release();
            float acc[4];
            exp_part<0, 16>(S, acc);
            l0 = acc[0] + acc[1]; l1 = acc[2] + acc[3];
            cvt_p(S, P);
        }
        uint32_t ready = 0;
        auto step = [&](auto first, bool store_prev, __nv_bfloat16* orow, bool swap_l, bool new_q) {
            constexpr bool FIRST = decltype(first)::value;
            if (!ready) mbar_wait(bar_full + 8 * r.slot, r.phase);
            bar_sync(my_bar, 256);
            wg_fence();
            issue_qk(S, qf, k_desc(r.desc));
            wg_commit();
            if (FIRST) {
                if (store_prev) {
                    float i0, i1;
                    const bool ok = finish_l(lo0, lo1, i0, i1);
                    if (!store_o(O, i0, i1, orow) || !ok) redo[tk - 1] = 1;
                }
                fence_regs(O);
                wg_fence();
            }
            issue_pv(O, P, v_desc(r.desc + (TILE_BYTES >> 4)), !FIRST);
            wg_commit();
            bar_arrive(other_bar, 256);
            wg_wait<1>();
            fence_regs(S);
            if (!FIRST && new_q) { fence_regs(qf); reload_q(); }
            float acc[4];
            exp_part<0, PIN_J>(S, acc);
            pin((acc[0] + acc[1]) + (acc[2] + acc[3]));
            wg_wait<0>();
            fence_regs(O);
            fence_regs(P);
            release();
            ready = mbar_test(bar_full + 8 * r.slot, r.phase);
            exp_part<PIN_J, 16>(S, acc);
            cvt_p(S, P);
            if (!FIRST && swap_l) { lo0 = l0; lo1 = l1; l0 = 0.f; l1 = 0.f; }
            l0 += acc[0] + acc[1]; l1 += acc[2] + acc[3];
        };
        __nv_bfloat16* oprev = out;
        while (true) {
            const int tn = t + nclusters;
            const bool has_next = tn < NTILES;
            step(IC<1>{}, tk > 0, oprev, false, false);
            const int jend = has_next ? NBLK : NBLK - 1;
#pragma unroll 1
            for (int j = 1; j < jend; j++) step(IC<0>{}, false, nullptr, j == NBLK - 1, has_next && j == NBLK - 2);
            oprev = out + (size_t)(t * 256 + row_in_tile) * DH + coff;
            if (has_next) {
                t = tn; tk++;
            } else {
                mbar_wait(bar_full + 8 * r.slot, r.phase);
                bar_sync(my_bar, 256);
                wg_fence();
                issue_pv(O, P, v_desc(r.desc + (TILE_BYTES >> 4)), 1);
                wg_commit();
                if (w == 0) bar_arrive(other_bar, 256);
                wg_wait<0>();
                fence_regs(O);
                float i0, i1;
                const bool ok = finish_l(l0, l1, i0, i1);
                if (!store_o(O, i0, i1, oprev) || !ok) redo[tk] = 1;
                break;
            }
        }
        bar_sync(3, 288);
        uint32_t n = 0;
        for (int tt = cluster_id, k = 0; tt < NTILES; tt += nclusters, k++) {
            if (!redo[k]) continue;
            mbar_wait(bar_qfull, qphase);
            qphase ^= 1;
            float m0 = -INFINITY, m1 = -INFINITY;
            l0 = 0.f; l1 = 0.f;
#pragma unroll 1
            for (int j = 0; j < NBLK; j++) {
                load_q(qf, qrow, qsw);
                mbar_wait(bar_rfull + 8 * (n & 1), (n >> 1) & 1);
                wg_fence();
                issue_qk(S, qf, k_desc(tile_desc(sb + (n & 1) * TILE_BYTES)));
                wg_commit();
                wg_wait<0>();
                fence_regs(S);
                if (warp == 0 && lane == 0) mbar_arrive(bar_rempty + 8 * (n & 1));
                n++;
                float a0 = m0, a1 = m1;
#pragma unroll
                for (int i = 0; i < 16; i++) {
                    a0 = fmaxf(a0, fmaxf(S[4 * i], S[4 * i + 1]));
                    a1 = fmaxf(a1, fmaxf(S[4 * i + 2], S[4 * i + 3]));
                }
                a0 = fmaxf(a0, __shfl_xor_sync(0xffffffffu, a0, 1)); a1 = fmaxf(a1, __shfl_xor_sync(0xffffffffu, a1, 1));
                a0 = fmaxf(a0, __shfl_xor_sync(0xffffffffu, a0, 2)); a1 = fmaxf(a1, __shfl_xor_sync(0xffffffffu, a1, 2));
                const float al0 = ex2(m0 - a0), al1 = ex2(m1 - a1);
                m0 = a0; m1 = a1;
#pragma unroll
                for (int i = 0; i < 16; i++) {
                    S[4 * i] -= a0; S[4 * i + 1] -= a0; S[4 * i + 2] -= a1; S[4 * i + 3] -= a1;
                    O[4 * i] *= al0; O[4 * i + 1] *= al0; O[4 * i + 2] *= al1; O[4 * i + 3] *= al1;
                }
                float acc[4];
                exp_part<0, 16>(S, acc);
                l0 = l0 * al0 + (acc[0] + acc[1]); l1 = l1 * al1 + (acc[2] + acc[3]);
                cvt_p(S, P);
                mbar_wait(bar_rfull + 8 * (n & 1), (n >> 1) & 1);
                wg_fence();
                issue_pv(O, P, v_desc(tile_desc(sb + (n & 1) * TILE_BYTES)), j != 0);
                wg_commit();
                wg_wait<0>();
                fence_regs(O);
                if (warp == 0 && lane == 0) mbar_arrive(bar_rempty + 8 * (n & 1));
                n++;
            }
            __syncwarp();
            if (lane == 0) mbar_arrive(bar_qempty);
            {
                float i0, i1;
                finish_l(l0, l1, i0, i1);
                store_o(O, i0, i1, out + (size_t)(tt * 256 + row_in_tile) * DH + coff);
            }
        }
        cluster_arrive(); cluster_wait();
    }
}

}

extern "C" void kernel_launch(void* const* d_in, const int* in_sizes, int n_in, void* d_out, int out_size) {
    const __nv_bfloat16* q = (const __nv_bfloat16*)d_in[0];
    const int* qk = (const int*)d_in[1];
    const int* qv = (const int*)d_in[2];
    const __nv_bfloat16* ks = (const __nv_bfloat16*)d_in[3];
    const __nv_bfloat16* kz = (const __nv_bfloat16*)d_in[4];
    const __nv_bfloat16* vs = (const __nv_bfloat16*)d_in[5];
    const __nv_bfloat16* vz = (const __nv_bfloat16*)d_in[6];
    typedef CUresult (*EncodeFn)(CUtensorMap*, CUtensorMapDataType, cuuint32_t, void*, const cuuint64_t*, const cuuint64_t*,
                                 const cuuint32_t*, const cuuint32_t*, CUtensorMapInterleave, CUtensorMapSwizzle,
                                 CUtensorMapL2promotion, CUtensorMapFloatOOBfill);
    static EncodeFn encode = nullptr;
    static int grid = 0;
    static Sched sc;
    if (grid == 0) {
        void* fn = nullptr;
        cudaDriverEntryPointQueryResult qr;
        cudaGetDriverEntryPoint("cuTensorMapEncodeTiled", &fn, cudaEnableDefault, &qr);
        encode = (EncodeFn)fn;
        cudaFuncSetAttribute(attn_kernel, cudaFuncAttributeMaxDynamicSharedMemorySize, SMEM_BYTES);
        cudaLaunchConfig_t cfg = {};
        cfg.gridDim = dim3(2, 1, 1); cfg.blockDim = dim3(384, 1, 1); cfg.dynamicSmemBytes = SMEM_BYTES;
        cudaLaunchAttribute at[1];
        at[0].id = cudaLaunchAttributeClusterDimension;
        at[0].val.clusterDim.x = 2; at[0].val.clusterDim.y = 1; at[0].val.clusterDim.z = 1;
        cfg.attrs = at; cfg.numAttrs = 1;
        int nc = 0;
        if (cudaOccupancyMaxActiveClusters(&nc, attn_kernel, &cfg) != cudaSuccess || nc <= 0) { nc = 1; (void)cudaGetLastError(); }
        if (nc > NTILES) nc = NTILES;
        if (FORCE_CLUSTERS) nc = FORCE_CLUSTERS;
        sc.rem = NTILES % nc;
        sc.nlight = sc.rem ? nc - sc.rem : 0;
        sc.bulk = sc.nlight >= MIN_LIGHT;
        const int lead = sc.bulk ? sc.rem : nc;
        sc.h0 = (lead + TILES_PER_HEAD - 1) / TILES_PER_HEAD;
        if (sc.h0 > HKV) sc.h0 = HKV;
        sc.h0inv = (65536 + sc.h0 - 1) / sc.h0;
        sc.nhelp = 2 * lead * 3;
        sc.nfirst = NITEMS;
        if (sc.bulk && ((sc.nhelp * NFIRST) & ~(ITEMS_PER_CHUNK - 1)) < NITEMS) sc.nfirst = (sc.nhelp * NFIRST) & ~(ITEMS_PER_CHUNK - 1);
        grid = nc * 2;
    }
    CUtensorMap qmap;
    const cuuint64_t dims[2] = {(cuuint64_t)DH, (cuuint64_t)HQ * SEQ};
    const cuuint64_t strides[1] = {(cuuint64_t)DH * 2};
    const cuuint32_t box[2] = {64, 128};
    const cuuint32_t estr[2] = {1, 1};
    encode(&qmap, CU_TENSOR_MAP_DATA_TYPE_BFLOAT16, 2, (void*)q, dims, strides, box, estr, CU_TENSOR_MAP_INTERLEAVE_NONE,
           CU_TENSOR_MAP_SWIZZLE_128B, CU_TENSOR_MAP_L2_PROMOTION_L2_128B, CU_TENSOR_MAP_FLOAT_OOB_FILL_NONE);
    attn_kernel<<<grid, 384, SMEM_BYTES>>>(qmap, qk, qv, ks, kz, vs, vz, (__nv_bfloat16*)d_out, sc);
}
```
